```python
import torch

def _softmax(x, axis=-1):
    return torch.softmax(x, dim=axis)
def _gelu(x):
    return torch.nn.functional.gelu(x, approximate="tanh")
def _silu(x):
    return torch.nn.functional.silu(x)
def _sigmoid(x):
    return torch.sigmoid(x)
def _layernorm(x, axis=-1, eps=1e-5):
    m = x.mean(dim=axis, keepdim=True)
    v = x.var(dim=axis, keepdim=True, unbiased=False)
    return (x - m) / torch.sqrt(v + eps)
def _scatter_add(tgt, idx, src, axis=0):
    return tgt.clone().index_add_(axis, idx, src)
def _segment_sum(src, seg, n):
    out = torch.zeros((n,) + src.shape[1:], dtype=src.dtype)
    return out.index_add_(0, seg, src)
def _pad(x, pw):
    flat = tuple(v for pair in reversed(pw) for v in pair)
    return torch.nn.functional.pad(x, flat)

kernel_name = 'standalone__weight_only_int_quip__prompt'

def setup_inputs():

    _w = (lambda a: (lambda t: t.to(torch.bfloat16) if t.is_floating_point() else t)(torch.as_tensor(a)))
    B, S, D, F = 1, 2048, 448, 1792
    G = -1 if -1 > 0 else D
    D = (D // G) * G
    ng = D // G
    bits = 4 if 4 > 0 else 4
    qmax = 1 << bits
    qw = torch.randint(0, qmax, (D, F)).to(torch.int32)
    U, _ = (lambda *_a, **_k: torch.linalg.qr(*[torch.as_tensor(_x).float() for _x in _a], **_k))((lambda *s: torch.randn(*s, dtype=torch.bfloat16) * 0.05)(D, D))
    V, _ = (lambda *_a, **_k: torch.linalg.qr(*[torch.as_tensor(_x).float() for _x in _a], **_k))((lambda *s: torch.randn(*s, dtype=torch.bfloat16) * 0.05)(F, F))
    return {
        "x": _w((lambda *s: torch.randn(*s, dtype=torch.bfloat16) * 0.05)(B, S, D)),
        "qw": _w(qw),
        "scales": _w(torch.abs((lambda *s: torch.randn(*s, dtype=torch.bfloat16) * 0.05)(ng, F)) * 0.02 + 0.005),
        "zeros": _w(torch.full((ng, F), qmax / 2.0, dtype=float)),
        "U": _w(U.to(float)),
        "V": _w(V.to(float)),
    }

def reference(x, qw, scales, zeros, U, V):
    B, S, D = x.shape
    ng, F = scales.shape
    G = D // ng
    s = (lambda x, n, axis: torch.repeat_interleave(x, n, dim=axis))(scales, G, axis=0)
    z = (lambda x, n, axis: torch.repeat_interleave(x, n, dim=axis))(zeros, G, axis=0)
    wq = ((lambda x, dt: x.to(dt))(qw, x.dtype) - z) * s
    xr = torch.einsum("bsd,de->bse", x, U)
    h  = torch.einsum("bse,ef->bsf", xr, wq)
    y  = torch.einsum("bsf,fg->bsg", h, V)
    return y
```

```cpp
#include <cuda_runtime.h>
#include <cuda_bf16.h>
#include <cuda.h>
#include <stdint.h>

namespace {

constexpr int S_ = 2048, D_ = 448, F_ = 1792;
constexpr int NCTA = 132;
constexpr int NTHREADS = 384;
constexpr uint32_t SB = 1024;
constexpr uint32_t BLK = 57344;
constexpr uint32_t STAGE = 20480;
constexpr uint32_t XSTAGE = 32768;
constexpr uint32_t BAR = SB + 4 * BLK;
constexpr uint32_t B_FULL1 = BAR, B_FIRST = BAR + 112, B_FULL = BAR + 120, B_EPOCH = BAR + 184, B_ZOK = BAR + 192, B_EMPTY = BAR + 200, B_REL1 = BAR + 232,
                   B_DONE = BAR + 256, B_SZ = BAR + 296, EPOCH = BAR + 304, SZ = BAR + 320, DBG = SZ + 1792;
constexpr int SMEM_BYTES = DBG + 256 - SB;
__host__ __device__ constexpr uint32_t stage_at(int u) { return (u < 3 ? u + 8 : u - 3) * STAGE; }
#define TGAP 350
#define TGAP2 200
#define TSW 7
#define XGAP 400
#define BGAP 900
#define C0MODE 1
#define C0AT 10
#define C0STEP 4
#define C3LATE 0
#define PKIND 0
#define PSPAN 3
#define PSLEEP 0
#define QA 0
#define QB 0
#define START 1
#define RGAP 150
#define RGAP0 100
#define RGAP3 0
#define ZMODE 1
#define ZGAP 320
#define ZGAP0 500
__host__ __device__ constexpr int kstep2(int i) { return i < 16 ? (i >> 3) * 14 + (i & 7) : (i - 16) / 6 * 14 + 8 + (i - 16) % 6; }

constexpr int C_TICKET = 0, C_T = 1, C_X = 29, C_ZERO = 61, C_COUNT = 93;

struct Scratch {
    __nv_bfloat16 T[56 * 448 * 32];
    uint4 xr[32 * 28 * 128];
    unsigned cnt[C_COUNT * 32];
};
__device__ __align__(1024) Scratch g_scratch;
#define TS(i) do {} while (0)
#define TS2(i) do {} while (0)

enum { JOB_A = 0, JOB_C = 1, JOB_D = 2, JOB_X = 3 };

struct Params {
    Scratch* scr;
    const __nv_bfloat16* scales;
    const __nv_bfloat16* zeros;
    __nv_bfloat16* y;
    uint32_t role[NCTA];
    uint32_t sched[4][2];
    uint32_t fills[4];
    uint32_t blks[8];
    CUtensorMap mapA[4], mapB[4];
    CUtensorMap vB, uB;
};

__device__ __forceinline__ bool elect() {
    uint32_t p;
    asm volatile("{\n.reg .pred p;\nelect.sync _|p, 0xffffffff;\nselp.u32 %0, 1, 0, p;\n}" : "=r"(p));
    return p;
}
__device__ __forceinline__ void mbar_init(uint32_t bar, uint32_t cnt) { asm volatile("mbarrier.init.shared::cta.b64 [%0], %1;" ::"r"(bar), "r"(cnt) : "memory"); }
__device__ __forceinline__ void mbar_init_fence() { asm volatile("fence.mbarrier_init.release.cluster;" ::: "memory"); }
__device__ __forceinline__ void mbar_expect_tx(uint32_t bar, uint32_t bytes) { asm volatile("mbarrier.arrive.expect_tx.shared::cta.b64 _, [%0], %1;" ::"r"(bar), "r"(bytes) : "memory"); }
__device__ __forceinline__ void mbar_arrive(uint32_t bar) { asm volatile("mbarrier.arrive.shared::cta.b64 _, [%0];" ::"r"(bar) : "memory"); }
__device__ __forceinline__ void mbar_arrive_n(uint32_t bar, uint32_t n) { asm volatile("mbarrier.arrive.shared::cta.b64 _, [%0], %1;" ::"r"(bar), "r"(n) : "memory"); }
__device__ __forceinline__ void mbar_wait(uint32_t bar, uint32_t parity) {
    asm volatile("{\n.reg .pred p;\n.reg .u32 c;\nmov.u32 c, 0;\n"
                 "W_%=:\nmbarrier.try_wait.parity.shared::cta.b64 p, [%0], %1;\nadd.u32 c, c, 1;\nsetp.gt.or.u32 p, c, 0x80000, p;\n@!p bra.uni W_%=;\n}"
                 ::"r"(bar), "r"(parity) : "memory");
}
__device__ __forceinline__ void mbar_wait_unless(uint32_t ok, uint32_t bar, uint32_t parity) {
    asm volatile("{\n.reg .pred p;\n.reg .u32 c;\nsetp.ne.u32 p, %2, 0;\n@p bra.uni D_%=;\nmov.u32 c, 0;\n"
                 "W_%=:\nmbarrier.try_wait.parity.shared::cta.b64 p, [%0], %1;\nadd.u32 c, c, 1;\nsetp.gt.or.u32 p, c, 0x80000, p;\n@!p bra.uni W_%=;\nD_%=:\n}"
                 ::"r"(bar), "r"(parity), "r"(ok) : "memory");
}
__device__ __forceinline__ uint32_t mbar_try(uint32_t bar, uint32_t parity) {
    uint32_t ok;
    asm volatile("{\n.reg .pred p;\nmbarrier.test_wait.parity.shared::cta.b64 p, [%1], %2;\nselp.u32 %0, 1, 0, p;\n}" : "=r"(ok) : "r"(bar), "r"(parity) : "memory");
    return ok;
}
__device__ __forceinline__ void tma2(uint32_t dst, const CUtensorMap* m, int c0, int c1, uint32_t bar) {
    asm volatile("cp.async.bulk.tensor.2d.shared::cluster.global.mbarrier::complete_tx::bytes [%0], [%1, {%3, %4}], [%2];" ::"r"(dst), "l"(m), "r"(bar), "r"(c0), "r"(c1) : "memory");
}
__device__ __forceinline__ void tma5(uint32_t dst, const CUtensorMap* m, int c0, int c2, int c4, uint32_t bar) {
    asm volatile("cp.async.bulk.tensor.5d.shared::cluster.global.mbarrier::complete_tx::bytes [%0], [%1, {%3, %6, %4, %6, %5}], [%2];" ::"r"(dst), "l"(m), "r"(bar), "r"(c0), "r"(c2), "r"(c4), "r"(0) : "memory");
}
__device__ __forceinline__ void bulk_load(uint32_t dst, const void* src, uint32_t bytes, uint32_t bar) {
    asm volatile("cp.async.bulk.shared::cluster.global.mbarrier::complete_tx::bytes [%0], [%1], %2, [%3];" ::"r"(dst), "l"(src), "r"(bytes), "r"(bar) : "memory");
}
__device__ __forceinline__ void fence_gpu() { asm volatile("fence.proxy.async;" ::: "memory"); }
__device__ __forceinline__ void signal(unsigned* p, unsigned n) { asm volatile("red.relaxed.gpu.global.add.u32 [%0], %1;" ::"l"(p), "r"(n) : "memory"); }
__device__ __forceinline__ void poll_ge(const unsigned* p, unsigned target) {
#pragma unroll 1
    for (int it = 0;; it++) {
        unsigned v;
        asm volatile("ld.relaxed.gpu.global.u32 %0, [%1];" : "=r"(v) : "l"(p) : "memory");
        if ((int)(v - target) >= 0) break;
        if (it > (1 << 20)) __trap();
    }
}
__device__ __forceinline__ void poll_lanes(const unsigned* p, unsigned target, uint32_t& seen, int need) {
#pragma unroll 1
    for (int it = 0; !((seen >> need) & 1); it++) {
        unsigned v = target - 1;
        const int l = threadIdx.x & 31;
        if (l >= need && l <= need + PSPAN && l < 4) {
            if (PKIND == 0) asm volatile("ld.relaxed.gpu.global.u32 %0, [%1];" : "=r"(v) : "l"(p) : "memory");
            if (PKIND == 1) asm volatile("ld.relaxed.sys.global.u32 %0, [%1];" : "=r"(v) : "l"(p) : "memory");
            if (PKIND == 2) asm volatile("atom.relaxed.gpu.global.or.b32 %0, [%1], 0;" : "=r"(v) : "l"(p) : "memory");
            if (PKIND == 3) asm volatile("ld.relaxed.gpu.global.L1::no_allocate.L2::evict_first.u32 %0, [%1];" : "=r"(v) : "l"(p) : "memory");
        }
        if (PSLEEP) __nanosleep(PSLEEP);
        seen = __ballot_sync(0xffffffffu, (int)(v - target) >= 0);
        if (it > (1 << 20)) __trap();
    }
}
__device__ __forceinline__ uint32_t clock32() {
    uint32_t c;
    asm volatile("mov.u32 %0, %%clock;" : "=r"(c));
    return c;
}
__device__ __forceinline__ void align_clock(uint32_t q) {
    if (q) {
        const uint32_t t = (clock32() | (q - 1)) + 1;
        while ((int)(clock32() - t) < 0) {}
    }
}
__device__ __forceinline__ void bar_sync(int id) { asm volatile("bar.sync %0, 256;" ::"r"(id) : "memory"); }
__device__ __forceinline__ void bar_arrive(int id) { asm volatile("bar.arrive %0, 256;" ::"r"(id) : "memory"); }
__device__ __forceinline__ void wg_fence() { asm volatile("wgmma.fence.sync.aligned;" ::: "memory"); }
__device__ __forceinline__ void wg_commit() { asm volatile("wgmma.commit_group.sync.aligned;" ::: "memory"); }
template <int N> __device__ __forceinline__ void wg_wait() { asm volatile("wgmma.wait_group.sync.aligned %0;" ::"n"(N) : "memory"); }
__device__ __forceinline__ uint4 lds128(uint32_t a) {
    uint4 v;
    asm volatile("ld.shared.v4.u32 {%0,%1,%2,%3}, [%4];" : "=r"(v.x), "=r"(v.y), "=r"(v.z), "=r"(v.w) : "r"(a) : "memory");
    return v;
}
#define U4O(v) "=r"(v.x), "=r"(v.y), "=r"(v.z), "=r"(v.w)
#define U4IO(v) "+r"(v.x), "+r"(v.y), "+r"(v.z), "+r"(v.w)
__device__ __forceinline__ void lds4_if(uint32_t ok, uint4& a, uint4& b, uint4& c, uint4& d, uint32_t q0, uint32_t q1) {
    asm volatile("{\n.reg .pred p;\nsetp.ne.u32 p, %16, 0;\n"
                 "@p ld.shared.v4.u32 {%0,%1,%2,%3}, [%17];\n@p ld.shared.v4.u32 {%4,%5,%6,%7}, [%17+1024];\n"
                 "@p ld.shared.v4.u32 {%8,%9,%10,%11}, [%18];\n@p ld.shared.v4.u32 {%12,%13,%14,%15}, [%18+1024];\n}"
                 : U4O(a), U4O(b), U4O(c), U4O(d) : "r"(ok), "r"(q0), "r"(q1) : "memory");
}
__device__ __forceinline__ void wait_lds4_unless(uint32_t ok, uint32_t bar, uint4& a, uint4& b, uint4& c, uint4& d, uint32_t q0, uint32_t q1) {
    asm volatile("{\n.reg .pred p;\n.reg .u32 c;\nsetp.ne.u32 p, %16, 0;\n@p bra.uni D_%=;\nmov.u32 c, 0;\n"
                 "W_%=:\nmbarrier.try_wait.parity.shared::cta.b64 p, [%19], 0;\nadd.u32 c, c, 1;\nsetp.gt.or.u32 p, c, 0x80000, p;\n@!p bra.uni W_%=;\n"
                 "ld.shared.v4.u32 {%0,%1,%2,%3}, [%17];\nld.shared.v4.u32 {%4,%5,%6,%7}, [%17+1024];\n"
                 "ld.shared.v4.u32 {%8,%9,%10,%11}, [%18];\nld.shared.v4.u32 {%12,%13,%14,%15}, [%18+1024];\nD_%=:\n}"
                 : U4IO(a), U4IO(b), U4IO(c), U4IO(d) : "r"(ok), "r"(q0), "r"(q1), "r"(bar) : "memory");
}
__device__ __forceinline__ uint32_t lds32(uint32_t a) {
    uint32_t v;
    asm volatile("ld.shared.u32 %0, [%1];" : "=r"(v) : "r"(a) : "memory");
    return v;
}
__device__ __forceinline__ void stg128(void* p, uint32_t x, uint32_t y, uint32_t z, uint32_t w) {
    asm volatile("st.global.v4.u32 [%0], {%1,%2,%3,%4};" ::"l"(p), "r"(x), "r"(y), "r"(z), "r"(w) : "memory");
}
__device__ __forceinline__ void red128(void* p, uint32_t x, uint32_t y, uint32_t z, uint32_t w) {
    asm volatile("red.relaxed.gpu.global.add.noftz.v4.bf16x2 [%0], {%1,%2,%3,%4};" ::"l"(p), "r"(x), "r"(y), "r"(z), "r"(w) : "memory");
}
__device__ __forceinline__ uint32_t pack_bf16(float lo, float hi) {
    uint32_t r;
    asm("cvt.rn.bf16x2.f32 %0, %1, %2;" : "=r"(r) : "f"(hi), "f"(lo));
    return r;
}
__device__ __forceinline__ uint32_t dequant2(uint32_t q0, uint32_t q1, uint32_t z, uint32_t s) {
    uint32_t p = pack_bf16(__int2float_rn((int)q0), __int2float_rn((int)q1)), r;
    asm("sub.rn.bf16x2 %0, %1, %2;" : "=r"(r) : "r"(p), "r"(z));
    asm("mul.rn.bf16x2 %0, %1, %2;" : "=r"(p) : "r"(r), "r"(s));
    return p;
}
__device__ __forceinline__ uint32_t bdesc(uint32_t addr, uint32_t lbo) { return (addr >> 4) | ((lbo >> 4) << 16); }
constexpr uint32_t HI128 = 0x40000040, HI64 = 0x80000020;

#define R8(d, o) "=&r"(d[o]), "=&r"(d[o + 1]), "=&r"(d[o + 2]), "=&r"(d[o + 3]), "=&r"(d[o + 4]), "=&r"(d[o + 5]), "=&r"(d[o + 6]), "=&r"(d[o + 7])
#define F8(d, o) "+f"(d[o]), "+f"(d[o + 1]), "+f"(d[o + 2]), "+f"(d[o + 3]), "+f"(d[o + 4]), "+f"(d[o + 5]), "+f"(d[o + 6]), "+f"(d[o + 7])
template <int N, uint32_t HI> __device__ __forceinline__ void mma(float (&d)[N / 2], const uint32_t* a, uint32_t b, int acc) {
    if constexpr (N == 128)
        asm volatile("{\n.reg .pred p;\n.reg .b64 bd;\nsetp.ne.b32 p, %69, 0;\nmov.b64 bd, {%68, %70};\n"
                     "wgmma.mma_async.sync.aligned.m64n128k16.f32.bf16.bf16 "
                     "{%0,%1,%2,%3,%4,%5,%6,%7,%8,%9,%10,%11,%12,%13,%14,%15,%16,%17,%18,%19,%20,%21,%22,%23,%24,%25,%26,%27,%28,%29,%30,%31,"
                     "%32,%33,%34,%35,%36,%37,%38,%39,%40,%41,%42,%43,%44,%45,%46,%47,%48,%49,%50,%51,%52,%53,%54,%55,%56,%57,%58,%59,%60,%61,%62,%63}, "
                     "{%64,%65,%66,%67}, bd, p, 1, 1, 1;\n}\n"
                     : F8(d, 0), F8(d, 8), F8(d, 16), F8(d, 24), F8(d, 32), F8(d, 40), F8(d, 48), F8(d, 56)
                     : "r"(a[0]), "r"(a[1]), "r"(a[2]), "r"(a[3]), "r"(b), "r"(acc), "n"(HI));
    else if constexpr (N == 64)
        asm volatile("{\n.reg .pred p;\n.reg .b64 bd;\nsetp.ne.b32 p, %37, 0;\nmov.b64 bd, {%36, %38};\n"
                     "wgmma.mma_async.sync.aligned.m64n64k16.f32.bf16.bf16 "
                     "{%0,%1,%2,%3,%4,%5,%6,%7,%8,%9,%10,%11,%12,%13,%14,%15,%16,%17,%18,%19,%20,%21,%22,%23,%24,%25,%26,%27,%28,%29,%30,%31}, "
                     "{%32,%33,%34,%35}, bd, p, 1, 1, 1;\n}\n"
                     : F8(d, 0), F8(d, 8), F8(d, 16), F8(d, 24)
                     : "r"(a[0]), "r"(a[1]), "r"(a[2]), "r"(a[3]), "r"(b), "r"(acc), "n"(HI));
    else
        asm volatile("{\n.reg .pred p;\n.reg .b64 bd;\nsetp.ne.b32 p, %21, 0;\nmov.b64 bd, {%20, %22};\n"
                     "wgmma.mma_async.sync.aligned.m64n32k16.f32.bf16.bf16 "
                     "{%0,%1,%2,%3,%4,%5,%6,%7,%8,%9,%10,%11,%12,%13,%14,%15}, "
                     "{%16,%17,%18,%19}, bd, p, 1, 1, 1;\n}\n"
                     : F8(d, 0), F8(d, 8)
                     : "r"(a[0]), "r"(a[1]), "r"(a[2]), "r"(a[3]), "r"(b), "r"(acc), "n"(HI));
}

template <int N, bool P2, class F, class G>
__device__ __forceinline__ void run_block(float (&acc)[N / 2], uint32_t (&A)[112], uint32_t buf, int wg, F mid, G tail) {
    const uint32_t d0 = bdesc(buf, BLK / 2);
    wg_fence();
#pragma unroll
    for (int i = 0; i < 28; i++) {
        if (!P2) mid(i);
        if (i == 26) bar_arrive(2 - wg);
        mma<N, P2 ? HI64 : HI128>(acc, &A[4 * i], d0 + (P2 ? kstep2(i) * 64 : i * 128), i > 0);
    }
    wg_commit();
    tail();
    wg_wait<0>();
}

template <int NH> __device__ __forceinline__ void pack_rows(const float* acc, uint32_t* v) {
#pragma unroll
    for (int i = 0; i < 2 * NH; i++) {
        const float* a = acc + (NH == 2 ? (i & 1) * 16 + (i >> 1) * 2 : i * 2);
#pragma unroll
        for (int j = 0; j < 4; j++) v[4 * i + j] = pack_bf16(a[4 * j], a[4 * j + 1]);
    }
}
template <int NH> __device__ __forceinline__ void store_y(const float* acc, char* p) {
    uint32_t v[8 * NH];
    pack_rows<NH>(acc, v);
#pragma unroll
    for (int i = 0; i < 2 * NH; i++) stg128(p + (NH == 2 ? (i & 1) * 64 + (i >> 1) * 16 * F_ : i * 16 * F_), v[4 * i], v[4 * i + 1], v[4 * i + 2], v[4 * i + 3]);
}
__device__ __forceinline__ void add_tile(const uint32_t* v, char* p, uint32_t gap) {
    const uint32_t t = clock32();
#pragma unroll
    for (int i = 0; i < 4; i++) {
        if (i) while (clock32() - t < i * gap) {}
        red128(p + (i & 1) * (BLK / 2) + (i >> 1) * 512, v[4 * i], v[4 * i + 1], v[4 * i + 2], v[4 * i + 3]);
    }
}
template <int NSTEP> __device__ __forceinline__ void store_frag(const float* acc, uint4* p) {
#pragma unroll
    for (int s = 0; s < NSTEP; s++)
        stg128(p + s * 128, pack_bf16(acc[8 * s], acc[8 * s + 1]), pack_bf16(acc[8 * s + 2], acc[8 * s + 3]),
               pack_bf16(acc[8 * s + 4], acc[8 * s + 5]), pack_bf16(acc[8 * s + 6], acc[8 * s + 7]));
}
__device__ __forceinline__ void warp_arrive(uint32_t bar, uint32_t n) {
    __syncwarp();
    if (elect()) mbar_arrive_n(bar, n);
}
template <int I0, int I1> __device__ __forceinline__ void lds_frags(uint32_t (&A)[112], uint32_t a) {
#pragma unroll
    for (int i = I0; i < I1; i++)
        asm volatile("ld.shared.v4.u32 {%0,%1,%2,%3}, [%4];" : "=r"(A[4 * i]), "=r"(A[4 * i + 1]), "=r"(A[4 * i + 2]), "=r"(A[4 * i + 3]) : "r"(a + i * 2048) : "memory");
}

template <bool BY_SMID>
__global__ void __launch_bounds__(NTHREADS, 1) quip_kernel(const __grid_constant__ Params p) {
    const int tid = threadIdx.x, lane = tid & 31;
    uint32_t smid;
    if (BY_SMID) asm volatile("mov.u32 %0, %%smid;" : "=r"(smid));
    else asm volatile("mov.u32 %0, %%ctaid.x;" : "=r"(smid));
    const uint32_t role = __shfl_sync(0xffffffffu, p.role[smid + (tid >> 9)], 0);
    const int warp = __shfl_sync(0xffffffffu, tid >> 5, 0);
    const bool loader = warp == 8 || warp == 11;
    const int odd = warp & 1;
    const int job = role & 3, kq = (role >> 2) & 3, G = (role >> 4) & 7, arow = (role >> 7) & 31;
    const int mt = (role >> 12) & 15, jt = (role >> 16) & 7;
    const bool has_p2 = (role >> 19) & 1, isx = job == JOB_X;
    auto load_stage = [&](int u) {
        const uint32_t dst = SB + (isx ? u * XSTAGE : stage_at(u)), fb = B_FULL1 + 8 * u;
        const int k = isx ? u * 64 : kq * 448 + u * 32;
        tma2(dst + (isx ? 16384 : job == JOB_A ? 4096 : 8192), &p.mapA[job], k, arow * 64, fb);
        tma5(dst, &p.mapB[job], isx ? kq * 112 : 0, k >> 3, G, fb);
        TS2(42 + u);
    };
    if (warp == 8) {
        if (elect()) {
            TS(34);
            mbar_init(B_FULL1, 1);
            mbar_init_fence();
            load_stage(0);
            TS(35);
        }
    } else if (warp == 9) {
        if (elect()) {
            mbar_init(B_SZ, 1);
            mbar_init_fence();
            mbar_expect_tx(B_SZ, 1792);
            bulk_load(SZ, p.zeros + kq * 448, 896, B_SZ);
            bulk_load(SZ + 896, p.scales + kq * 448, 896, B_SZ);
            TS(36);
        }
    }
    const uint32_t c0 = clock32() - (warp == 8 ? 150 : 0);

    if (warp < 8) {
        asm volatile("setmaxnreg.inc.sync.aligned.u32 232;");
        const int wg = warp >> 2, wq = warp & 3, wtid = tid & 127, r0 = wq * 16 + (lane >> 2);
        uint32_t sched = p.sched[job][wg];
        const bool idle1 = sched >> 28;
        uint32_t blks = p.blks[jt] | ((p.fills[job] >> (12 + 3 * wg)) << 24);
        asm volatile("" : "+r"(blks));
        uint32_t A[112];
        if (wg == 1) bar_arrive(1);
        asm volatile("bar.sync 4, 384;" ::: "memory");
#define CTS(i) do { if (wq == 0) TS((i) + 17 * wg); } while (0)
        uint32_t ok1 = 0, ok2 = 0;
        auto peek = [&](uint32_t sc) {
            ok1 = mbar_try(B_FULL + 16 * (sc & 3), (sc >> 2) & 1);
            ok2 = mbar_try(B_FULL + 8 + 16 * (sc & 3), (sc >> 2) & 1);
        };
        auto peek_next = [&]() { peek(sched >> 4); };
        auto next_block = [&]() -> uint32_t {
            mbar_wait_unless(ok1, B_FULL + 16 * (sched & 3), (sched >> 2) & 1);
            bar_sync(1 + wg);
            return SB + (sched & 3) * BLK;
        };
        auto half2 = [&](int i) {
            if (i == 14) {
                mbar_wait_unless(ok2, B_FULL + 8 + 16 * (sched & 3), (sched >> 2) & 1);
                wg_fence();
            }
        };
        uint32_t held[16];
        char* tp = nullptr;
        auto release_block = [&]() {
            if (elect()) mbar_arrive_n(B_EMPTY + 8 * (sched & 3), 1 + ((sched >> 3) & 1));
            sched >>= 4;
        };

        auto no_tile = [&]() {
#pragma unroll
            for (int i = 0; i < 16; i++) asm volatile("" : "=r"(held[i]));
        };
        if (idle1) {
            for (int b = 0; b < 3; b++) { bar_sync(2); bar_arrive(1); }
            no_tile();
        } else if (isx) {
            const uint32_t rowa = SB + 16384 + (wg * 64 + wq * 16 + (lane & 15)) * 128 + (((lane >> 4) ^ (lane & 7)) << 4);
            uint4* dst = p.scr->xr + (arow + wg) * 28 * 128 + wtid;
            {
                float acc[64];
#pragma unroll
                for (int st = 0; st < 7; st++) {
                    mbar_wait(B_FULL1 + 8 * st, 0);
                    if (st == 0) CTS(0);
#pragma unroll
                    for (int ks = 4 * st; ks < 4 * st + 4; ks++)
                        asm volatile("ldmatrix.sync.aligned.m8n8.x4.shared.b16 {%0,%1,%2,%3}, [%4];"
                                     : "=r"(A[4 * ks]), "=r"(A[4 * ks + 1]), "=r"(A[4 * ks + 2]), "=r"(A[4 * ks + 3])
                                     : "r"((rowa ^ ((ks & 3) << 5)) + st * XSTAGE) : "memory");
                    wg_fence();
#pragma unroll
                    for (int ks = 0; ks < 4; ks++) mma<128, HI128>(acc, &A[16 * st + 4 * ks], bdesc(SB + st * XSTAGE + ks * 2048, 8192), st + ks > 0);
                    wg_commit();
                    if (st == 2 || st == 4) {
                        wg_wait<1>();
                        if (elect()) mbar_arrive(B_EMPTY + 4 * (st - 2));
                    }
                    if (st == 2) CTS(13);
                    if (st == 4) CTS(14);
                }
                peek(sched);
                wg_wait<0>();
                if (elect()) { mbar_arrive(B_EMPTY + 16); mbar_arrive(B_EMPTY + 24); }
                CTS(1);
                uint32_t v[32];
#pragma unroll
                for (int i = 0; i < 32; i++) {
                    v[i] = pack_bf16(acc[2 * i], acc[2 * i + 1]);
                    asm volatile("" : "+r"(v[i]));
                }
                auto early = [&]() {
#pragma unroll
                    for (int s = 0; s < 8; s++) stg128(dst + (kq * 4 + s) * 128, v[4 * s], v[4 * s + 1], v[4 * s + 2], v[4 * s + 3]);
                    warp_arrive(B_DONE + 8, 1);
                };
                if (wg) early();
                CTS(2);
                float acc2[32];
                run_block<64, false>(acc2, A, next_block(), wg, half2, [&]() {
                    peek_next();
                    if (!wg) early();
                });
                release_block();
                CTS(5);
                store_frag<4>(acc2, dst + (16 + kq * 3) * 128);
            }
            {
                float acc[16];
                run_block<32, false>(acc, A, next_block() + 64, wg, half2, []() {});
                release_block();
                CTS(6);
                store_frag<2>(acc, dst + (20 + kq * 3) * 128);
                warp_arrive(B_DONE + 16, 1);
            }
            ok1 = 0;
            no_tile();
        } else {
            tp = reinterpret_cast<char*>(p.scr->T) + (job == JOB_C ? G + wg : G) * BLK + ((job == JOB_A ? arow + wg : arow) * 64 + r0) * 64 +
                       (((lane & 3) ^ (lane >> 3)) << 4);
            const uint32_t nrel1 = job == JOB_D ? 2 : 1;
            {
                const uint32_t q0 = SB + (job == JOB_A ? 4096 + wg * 8192 : 8192) + r0 * 128 + (((2 * (lane & 3)) ^ (lane >> 2)) << 4);
                const uint32_t q1 = q0 ^ 16;
                const uint32_t db = bdesc(SB + (job == JOB_C ? wg * 4096 : 0), 0);
                float acc[32];
                mbar_wait(B_SZ, 0);
#pragma unroll
                for (int i = 0; i < 28; i++) {
                    const uint4 v = lds128(SZ + (lane & 3) * 16 + (i & 1) * 896 + (i >> 1) * 64);
                    A[4 * i] = v.x; A[4 * i + 1] = v.y; A[4 * i + 2] = v.z; A[4 * i + 3] = v.w;
                }
                CTS(12);
                mbar_wait(B_FULL1, 0);
                CTS(0);
                if (warp == 0) TS2(32);
                constexpr uint32_t so0 = stage_at(0);
                uint4 l0 = lds128(q0 + so0), h0 = lds128(q0 + so0 + 1024), l1 = lds128(q1 + so0), h1 = lds128(q1 + so0 + 1024);
                uint32_t ok = mbar_try(B_FULL1 + 8, 0);
#pragma unroll
                for (int st = 0; st < 14; st++) {
                    const uint32_t so = stage_at(st + 1);
                    uint4 m0, i0, m1, i1;
                    if (st < 13) lds4_if(ok, m0, i0, m1, i1, q0 + so, q1 + so);
                    uint32_t ok2 = 0;
                    const uint32_t z0 = A[8 * st], z1 = A[8 * st + 1], z2 = A[8 * st + 2], z3 = A[8 * st + 3];
                    const uint32_t s0 = A[8 * st + 4], s1 = A[8 * st + 5], s2 = A[8 * st + 6], s3 = A[8 * st + 7];
                    A[8 * st + 0] = dequant2(l0.x, l0.y, z0, s0);
                    A[8 * st + 1] = dequant2(h0.x, h0.y, z0, s0);
                    A[8 * st + 2] = dequant2(l0.z, l0.w, z1, s1);
                    A[8 * st + 3] = dequant2(h0.z, h0.w, z1, s1);
                    A[8 * st + 4] = dequant2(l1.x, l1.y, z2, s2);
                    A[8 * st + 5] = dequant2(h1.x, h1.y, z2, s2);
                    A[8 * st + 6] = dequant2(l1.z, l1.w, z3, s3);
                    A[8 * st + 7] = dequant2(h1.z, h1.w, z3, s3);
                    if (st < 12) ok2 = mbar_try(B_FULL1 + 8 * (st + 2), 0);
                    wg_fence();
                    mma<64, HI128>(acc, &A[8 * st], db + (stage_at(st) >> 4), st > 0);
                    mma<64, HI128>(acc, &A[8 * st + 4], db + (stage_at(st) >> 4) + 128, 1);
                    wg_commit();
                    const int r = st - 1;
                    if ((r >= 0 && r < 3) || r == 5 || r == 8 || r == 11) {
                        wg_wait<1>();
                        if (elect()) mbar_arrive_n(r < 3 ? B_REL1 + 8 * r : B_EMPTY + 8 * ((r - 5) / 3), nrel1);
                    }
                    if (warp == 0) TS2(st);
                    if (st < 13) {
                        wait_lds4_unless(ok, B_FULL1 + 8 * (st + 1), m0, i0, m1, i1, q0 + so, q1 + so);
                        l0 = m0; h0 = i0; l1 = m1; h1 = i1;
                    }
                    if (warp == 0) TS2(16 + st);
                    ok = ok2;
                    if (st == 2) CTS(13);
                    if (st == 5) CTS(14);
                    if (st == 9) CTS(15);
                }
                mbar_wait(B_ZOK, 0);
                peek(sched);
                wg_wait<0>();
                if (elect()) mbar_arrive_n(B_EMPTY + 24, nrel1);
                CTS(1);
                pack_rows<2>(acc, held);
                if (wg || !C0MODE) {
                    add_tile(held, tp, wg ? RGAP0 : 0);
                    warp_arrive(B_DONE + 8, nrel1);
                }
                CTS(2);
            }
#pragma unroll 1
            for (int b = 1; b < 4; b++) {
                float acc[32];
                const uint32_t send = C0MODE && b == 1 && !wg;
                run_block<64, false>(acc, A, next_block(), wg, [&](int i) {
                    half2(i);
                    if (C0MODE && i >= C0AT && i < C0AT + 4 * C0STEP && (i - C0AT) % C0STEP == 0) {
                        const int g = (i - C0AT) / C0STEP;
                        asm volatile("{\n.reg .pred p;\nsetp.ne.u32 p, %5, 0;\n@p red.relaxed.gpu.global.add.noftz.v4.bf16x2 [%0], {%1,%2,%3,%4};\n}"
                                     ::"l"(tp + (g & 1) * (BLK / 2) + (g >> 1) * 512), "r"(held[4 * g]), "r"(held[4 * g + 1]), "r"(held[4 * g + 2]),
                                       "r"(held[4 * g + 3]), "r"(send) : "memory");
                        if (g == 3)
                            asm volatile("{\n.reg .pred p, q;\nelect.sync _|q, 0xffffffff;\nsetp.ne.and.u32 p, %2, 0, q;\n"
                                         "@p mbarrier.arrive.shared::cta.b64 _, [%0], %1;\n}" ::"r"(B_DONE + 8), "r"(nrel1), "r"(send) : "memory");
                    }
                }, peek_next);
                release_block();
                CTS(3 + b);
                tp += 7 * BLK;
                pack_rows<2>(acc, held);
                if (b < 3) {
                    add_tile(held, tp, RGAP);
                    warp_arrive(B_DONE + 8 + 8 * b, nrel1);
                }
            }
        }

        if (has_p2) {
            const uint32_t fa = blks >> 24, abar = B_FULL + 16 * (fa & 3), apar = (fa >> 2) & 1, asrc = SB + (fa & 3) * BLK + wtid * 16;
            mbar_wait(abar, apar);
            CTS(16);
            auto late = [&]() {
                mbar_wait(abar + 8, apar);
                lds_frags<16, 28>(A, asrc);
                if (elect()) mbar_arrive_n(B_EMPTY + 8 * (fa & 3), 2);
            };
            char* const yp = reinterpret_cast<char*>(p.y) + (mt * 128 + wg * 64 + r0) * (F_ * 2) + (lane & 3) * 16;
            auto tail = [&]() { ok1 = mbar_try(B_FULL + 16 * ((sched >> 4) & 3), (sched >> 6) & 1); };
            if (jt < 6) {
#pragma unroll
                for (int g = 0; g < 4; g++)
                    asm volatile("red.relaxed.gpu.global.add.noftz.v4.bf16x2 [%16], {%17,%18,%19,%20};\n"
                                 "ld.volatile.shared.v4.u32 {%0,%1,%2,%3}, [%21];\nld.volatile.shared.v4.u32 {%4,%5,%6,%7}, [%21+2048];\n"
                                 "ld.volatile.shared.v4.u32 {%8,%9,%10,%11}, [%21+4096];\nld.volatile.shared.v4.u32 {%12,%13,%14,%15}, [%21+6144];"
                                 : R8(A, 16 * g), R8(A, 16 * g + 8)
                                 : "l"(tp + (g & 1) * (BLK / 2) + (g >> 1) * 512), "r"(held[4 * g]), "r"(held[4 * g + 1]), "r"(held[4 * g + 2]),
                                   "r"(held[4 * g + 3]), "r"(asrc + g * 8192) : "memory");
                warp_arrive(B_DONE + 32, 1);
                if (!wg) asm volatile("bar.sync 7, 160;" ::: "memory");
                bar_sync(1 + wg);
                const uint32_t d0 = bdesc(SB + (sched & 3) * BLK, BLK / 2);
                float acc[32];
#pragma unroll
                for (int i = 0; i < 28; i++) {
                    if (i == 16) {
                        late();
                        bar_sync(1 + wg);
                    }
                    if (i % 4 == 0) wg_fence();
                    if (i == 14 || i == 26) bar_arrive(2 - wg);
                    mma<64, HI64>(acc, &A[4 * i], d0 + kstep2(i) * 64, i > 0);
                }
                wg_commit();
                tail();
                wg_wait<0>();
                CTS(7);
                store_y<2>(acc, yp + (blks & 63) * 64);
                sched >>= 4;
                blks >>= 6;
            } else {
                if (!isx && !idle1) {
                    add_tile(held, tp, 0);
                    warp_arrive(B_DONE + 32, 2);
                }
                lds_frags<0, 16>(A, asrc);
                late();
            }
#pragma unroll 1
            for (int b = jt < 6; b < 4; b++) {
                const uint32_t buf = next_block();
                if (b == (jt < 6)) {
                    float acc[16];
                    run_block<32, true>(acc, A, buf, wg, [](int) {}, tail);
                    CTS(7 + b);
                    store_y<1>(acc, yp + (blks & 63) * 64);
                } else {
                    float acc[32];
                    run_block<64, true>(acc, A, buf, wg, [](int) {}, tail);
                    CTS(7 + b);
                    store_y<2>(acc, yp + (blks & 63) * 64);
                }
                sched >>= 4;
                blks >>= 6;
            }
        }
        CTS(11);
    } else {
        asm volatile("setmaxnreg.dec.sync.aligned.u32 40;");
        unsigned* const cnt = p.scr->cnt;
        if (!loader) {
            if (!odd) {
                if (elect()) {
                    for (int i = 0; i < 10; i++) mbar_init(B_FULL + 8 * i, 1);
                    for (int i = 0; i < 12; i++) mbar_init(B_EMPTY + 8 * i, 8);
                    mbar_init_fence();
                }
                __syncwarp();
                asm volatile("bar.arrive 5, 96;" ::: "memory");
            }
            asm volatile("bar.sync 4, 384;" ::: "memory");
            unsigned* const zc = cnt + (C_ZERO + (role >> 20)) * 32;
            if (odd) {
                if (elect()) {
                    const unsigned epoch = atomicAdd(cnt + C_TICKET * 32, 1u) / NCTA;
                    asm volatile("st.shared.u32 [%0], %1;" ::"r"(EPOCH), "r"(epoch) : "memory");
                    mbar_arrive(B_EPOCH);
                }
                __syncwarp();
                if (!isx) {
                    mbar_wait(B_FULL1 + 8 * 5, 0);
                    poll_ge(zc, (lds32(EPOCH) + 1) * 4);
                    if (elect()) mbar_arrive(B_ZOK);
                    TS(49);
                }
            }
            else if (!isx) {
                char* z = reinterpret_cast<char*>(p.scr->T) + (kq * 7 + G) * BLK + arow * 4096 + lane * 16;
                const uint32_t w1 = job == JOB_A ? 4096 : job == JOB_C ? BLK : 0;
#pragma unroll 1
                for (uint32_t t = ZGAP0; t < ZGAP0 + 8 * ZGAP; t += ZGAP) {
                    while (clock32() - c0 < t) {}
                    stg128(z, 0, 0, 0, 0);
                    stg128(z + BLK / 2, 0, 0, 0, 0);
                    while (clock32() - c0 < t + ZGAP / 2) {}
                    stg128(z + w1, 0, 0, 0, 0);
                    stg128(z + w1 + BLK / 2, 0, 0, 0, 0);
                    z += 512;
                }
                __syncwarp();
            }
#pragma unroll 1
            for (int f = isx ? 2 - odd : odd; f < (isx ? 3 : 5); f += 2) {
                unsigned* c = f == 0 ? zc : cnt + (isx ? C_X + arow + f - 1 : C_T + (f - 1) * 7 + G) * 32;
                if (f) mbar_wait(B_DONE + 8 * f, 0);
                if (elect()) {
                    TS(50 + 2 * f);
                    fence_gpu();
                    signal(c, f && job == JOB_A ? 2 : 1);
                    if (f && job == JOB_C) signal(c + 32, 1);
                    TS(51 + 2 * f);
                }
                __syncwarp();
            }
        } else {
            if (elect()) {
                for (int i = 0; i < 7; i++) mbar_init(B_FULL1 + 16 * i + 16 - 8 * odd, 1);
                mbar_init_fence();
                for (int i = 0; i < 7; i++) mbar_expect_tx(B_FULL1 + 16 * i + 8 * odd, isx ? XSTAGE : STAGE - 4096 * job);
            }
            __syncwarp();
            asm volatile("bar.arrive 4, 384;" ::: "memory");
#pragma unroll 1
            for (int u = 2 - odd; u < (isx ? 7 : 14); u += 2) {
                if (u == 3 || u == 4) asm volatile("bar.sync 5, 96;" ::: "memory");
                if (u >= 11) mbar_wait(B_REL1 + 8 * (u - 11), 0);
                while (clock32() - c0 < (isx ? u * XGAP : min(u * TGAP, TSW * (TGAP - TGAP2) + u * TGAP2))) {}
                if (elect()) load_stage(u);
            }
            if (!odd) {
                const int nb = isx ? 2 : job == JOB_C ? 6 : 3;
                if (elect()) asm volatile("prefetch.tensormap [%0];" ::"l"(&p.vB + isx) : "memory");
                const uint32_t c1 = clock32();
#pragma unroll 1
                for (int b = 0; b < nb; b++) {
                    const uint32_t dst = SB + (b & 3) * BLK, fb = B_FULL + 16 * (b & 3);
                    const int col = isx ? kq * 112 + 128 + b * 32 : (7 + G + (job == JOB_C ? (b >> 1) * 7 + (b & 1) : b * 7)) * 64;
                    mbar_wait(B_EMPTY + 8 * (b & 3), b >> 2);
                    if (!isx) while (clock32() - c1 < (job == JOB_C ? b >> 1 : b) * BGAP) {}
                    if (C3LATE && job != JOB_C && b == 2) mbar_wait(B_DONE + 8, 0), __nanosleep(C3LATE);
                    if (elect()) {
                        mbar_expect_tx(fb, BLK / 2);
                        mbar_expect_tx(fb + 8, BLK / 2);
                        tma5(dst, &p.vB + isx, col, 0, isx ? 0 : kq * 14, fb);
                        tma5(dst + BLK / 2, &p.vB + isx, col, 0, isx ? 7 : kq * 14 + 7, fb + 8);
                    }
                    if (b < 3) TS2(56 + b);
                }
                TS(40);
                if (has_p2) {
                    uint32_t blks = p.blks[jt], fills = p.fills[job];
                    mbar_wait(B_EPOCH, 0);
                    const unsigned target = (lds32(EPOCH) + 1) * 28;
                    const unsigned* fp = cnt + (C_T + ((blks >> (6 * (lane & 3) + 1)) & 31)) * 32;
                    uint32_t seen = 0;
#pragma unroll 1
                    for (int b = 0; b < 4; b++) {
                        const uint32_t hb = blks & 63, fb = b < (jt < 6) ? B_FIRST : B_FULL + 16 * (fills & 3), bytes = b == (jt < 6) ? BLK / 2 : BLK;
                        poll_lanes(fp, target, seen, b);
                        TS(41 + 2 * b);
                        mbar_wait(B_EMPTY + 8 * (fills & 3), (fills >> 2) & 1);
                        if (elect()) {
                            mbar_expect_tx(fb, bytes);
                            align_clock(QB);
                            bulk_load(SB + (fills & 3) * BLK, p.scr->T + hb * 14336, bytes, fb);
                        }
                        TS(42 + 2 * b);
                        blks >>= 6;
                        fills >>= 3;
                    }
                }
            } else {
                mbar_wait(B_EPOCH, 0);
                const unsigned epoch = lds32(EPOCH);
                if (has_p2) {
                    const uint32_t fills = p.fills[job] >> 12;
                    mbar_wait(B_DONE + 8, 0);
#pragma unroll 1
                    for (int i = 0; i < 4; i++) {
                        const int w = i & 1, late = i >> 1;
                        const uint32_t f = fills >> (3 * w), fb = B_FULL + 16 * (f & 3) + 8 * late, bytes = late ? 24576 : 32768;
                        if (!w) poll_ge(cnt + (C_X + mt * 2 + late) * 32, (epoch + 1) * 2);
                        if (!late) mbar_wait(B_EMPTY + 8 * (f & 3), (f >> 2) & 1);
                        if (elect()) {
                            mbar_expect_tx(fb, bytes);
                            if (i < 3) align_clock(QA);
                            bulk_load(SB + (f & 3) * BLK + late * 32768, p.scr->xr + ((mt * 2 + w) * 28 + late * 16) * 128, bytes, fb);
                        }
                        TS(60 + w * 2 + late);
                    }
                    if (jt < 6) {
                        mbar_wait(B_FIRST, 0);
                        asm volatile("bar.arrive 7, 160;" ::: "memory");
                        TS(38);
                    }
                } else {
                    poll_ge(cnt + C_TICKET * 32, (epoch + 1) * NCTA);
                }
            }
        }
    }
}

__device__ __nv_bfloat16 g_fb_xr[S_ * D_];
__device__ __nv_bfloat16 g_fb_T[D_ * F_];
template <int MODE>
__global__ void fb_gemm(const __nv_bfloat16* a, const int* q, const __nv_bfloat16* sc, const __nv_bfloat16* ze, const __nv_bfloat16* b,
                        __nv_bfloat16* c, int M, int N, int K) {
    if (MODE == 0) c = g_fb_xr;
    if (MODE == 1) c = g_fb_T;
    if (MODE == 2) { a = g_fb_xr; b = g_fb_T; }
    const int n = blockIdx.x * blockDim.x + threadIdx.x, m = blockIdx.y;
    if (n >= N) return;
    float acc = 0.f;
    for (int k = 0; k < K; k++) {
        const __nv_bfloat16 av = MODE == 1 ? __hmul(__hsub(__float2bfloat16((float)q[m * K + k]), ze[k]), sc[k]) : a[m * K + k];
        acc += __bfloat162float(av) * __bfloat162float(b[k * N + n]);
    }
    c[m * N + n] = __float2bfloat16(acc);
}

typedef CUresult (*EncodeFn)(CUtensorMap*, CUtensorMapDataType, cuuint32_t, void*, const cuuint64_t*, const cuuint64_t*, const cuuint32_t*,
                             const cuuint32_t*, CUtensorMapInterleave, CUtensorMapSwizzle, CUtensorMapL2promotion, CUtensorMapFloatOOBfill);

bool encode(EncodeFn fn, CUtensorMap* m, CUtensorMapDataType dt, int rank, const void* p, const cuuint64_t* dims, const cuuint64_t* strides,
            const cuuint32_t* box) {
    const cuuint32_t es[5] = {1, 1, 1, 1, 1};
    return fn(m, dt, rank, const_cast<void*>(p), dims, strides, box, es, CU_TENSOR_MAP_INTERLEAVE_NONE, CU_TENSOR_MAP_SWIZZLE_128B,
              CU_TENSOR_MAP_L2_PROMOTION_L2_128B, CU_TENSOR_MAP_FLOAT_OOB_FILL_NONE) == CUDA_SUCCESS;
}

uint32_t make_role(int sm) {
    const int t = sm >> 1;
    int gpc, ti;
    if (t < 32) { gpc = t & 7; ti = t >> 3; }
    else if (t < 60) { gpc = 1 + (t - 32) % 7; ti = 4 + (t - 32) / 7; }
    else if (t < 62) { gpc = t - 54; ti = 8; }
    else { gpc = 0; ti = t - 58; }
    const int idx = ti * 2 + (sm & 1), kq = gpc >> 1;
    auto tjob = [&](int job, int G, int dblk) { return (unsigned)(job | kq << 2 | G << 4 | dblk << 7); };
    auto xjob = [&](int xm, int xh) { return (unsigned)(JOB_X | xh << 3 | xm << 8); };
    unsigned r;
    if (gpc & 1) {
        if (idx < 12) r = tjob(JOB_A, idx & 3, (idx >> 2) * 2);
        else if (idx < 14) r = tjob(JOB_C, (idx - 12) * 2, 6);
        else r = xjob(((0xC852 >> (kq * 4)) & 15) + ((idx - 14) >> 1), idx & 1);
    } else {
        if (idx < 9) r = tjob(JOB_A, 4 + idx % 3, (idx / 3) * 2);
        else if (idx == 9) r = tjob(JOB_C, 4, 6);
        else if (idx == 10) r = tjob(JOB_D, 6, 6);
        else if (idx == 11) r = xjob(14 + (kq >> 1), kq & 1);
        else r = xjob(kq * 3 + ((idx - 12) >> 1), idx & 1);
    }
#define P2MAP 0
    const int n = gpc & 1 ? (idx < 14 ? 10 + idx : 16 + idx) : (idx < 10 ? idx : 14 + idx);
    int mt = kq * 4 + (n & 3), jt = (n >> 2) & 7;
    return r | mt << 12 | jt << 16 | (idx < 16) << 19 | (unsigned)((gpc & 1) * 16 + (idx & 15)) << 20;
}
uint32_t make_blks(int jt) {
    if (jt < 6) return (unsigned)(2 * jt | (14 + jt) << 6 | 2 * (14 + jt) << 12 | 2 * (21 + jt) << 18);
    return (unsigned)((6 + jt) | 2 * (2 * jt - 2) << 6 | 2 * (2 * jt - 1) << 12 | 2 * (jt == 6 ? 20 : 27) << 18);
}
uint32_t make_fills(int job) {
    const int a[6] = {3, 6, 0, 1, 4, 5}, c[6] = {0, 1, 2, 3, 6, 7}, x[6] = {3, 5, 6, 0, 2, 4};
    const int* f = job == JOB_C ? c : job == JOB_X ? x : a;
    unsigned s = 0;
    for (int i = 0; i < 6; i++) s |= (unsigned)f[i] << (3 * i);
    return s;
}
uint32_t make_sched(int job, int w) {
    const int priv = job == JOB_C || job == JOB_D, nb1 = job == JOB_D && w == 1 ? 0 : job == JOB_X ? 2 : 3;
    unsigned s = (unsigned)(nb1 == 0) << 28;
    for (int b = 0; b < nb1 + 4; b++) {
        const unsigned v = b >= nb1 ? (make_fills(job) >> (3 * (b - nb1))) & 7 : job == JOB_C ? 2 * b + w : b;
        s |= (v | (priv && b < nb1) << 3) << (4 * b);
    }
    return s;
}

}

extern "C" void kernel_launch(void* const* d_in, const int* in_sizes, int n_in, void* d_out, int out_size) {
    const __nv_bfloat16* x = (const __nv_bfloat16*)d_in[0];
    const int* qw = (const int*)d_in[1];
    const __nv_bfloat16* scales = (const __nv_bfloat16*)d_in[2];
    const __nv_bfloat16* zeros = (const __nv_bfloat16*)d_in[3];
    const __nv_bfloat16* U = (const __nv_bfloat16*)d_in[4];
    const __nv_bfloat16* V = (const __nv_bfloat16*)d_in[5];
    __nv_bfloat16* y = (__nv_bfloat16*)d_out;

    int dev = 0, sms = 0, reserved = 0;
    cudaGetDevice(&dev);
    cudaDeviceGetAttribute(&sms, cudaDevAttrMultiProcessorCount, dev);
    cudaDeviceGetAttribute(&reserved, cudaDevAttrReservedSharedMemoryPerBlock, dev);
    auto kern = sms == NCTA ? quip_kernel<true> : quip_kernel<false>;
    EncodeFn fn = nullptr;
    cudaDriverEntryPointQueryResult qr;
    bool ok = sms >= NCTA && reserved == (int)SB &&
              cudaGetDriverEntryPoint("cuTensorMapEncodeTiled", (void**)&fn, cudaEnableDefault, &qr) == cudaSuccess && fn != nullptr;
    ok = ok && cudaFuncSetAttribute(kern, cudaFuncAttributeMaxDynamicSharedMemorySize, SMEM_BYTES) == cudaSuccess;
    Params p;
    if (ok) {
        const auto BF = CU_TENSOR_MAP_DATA_TYPE_BFLOAT16;
        {
            const cuuint64_t dims[2] = {F_, D_}, st[1] = {F_ * 4};
            const cuuint32_t b128[2] = {32, 128}, b64[2] = {32, 64};
            ok = ok && encode(fn, &p.mapA[JOB_A], CU_TENSOR_MAP_DATA_TYPE_INT32, 2, qw, dims, st, b128);
            ok = ok && encode(fn, &p.mapA[JOB_C], CU_TENSOR_MAP_DATA_TYPE_INT32, 2, qw, dims, st, b64);
            const cuuint64_t dimx[2] = {D_, S_}, stx[1] = {D_ * 2};
            const cuuint32_t boxx[2] = {64, 128};
            ok = ok && encode(fn, &p.mapA[JOB_X], BF, 2, x, dimx, stx, boxx);
        }
        const cuuint32_t boxB[5] = {64, 2, 4, 4, 7};
        {
            const cuuint64_t r = F_ * 2;
            const cuuint64_t dimsE[5] = {64, 2, F_ / 8, 4, F_ / 64}, stE[4] = {r, 8 * r, 2 * r, 128};
            const cuuint32_t boxE1[5] = {64, 2, 4, 4, 1}, boxE2[5] = {64, 2, 4, 4, 2};
            ok = ok && encode(fn, &p.mapB[JOB_A], BF, 5, V, dimsE, stE, boxE1);
            ok = ok && encode(fn, &p.mapB[JOB_C], BF, 5, V, dimsE, stE, boxE2);
            const cuuint64_t dimsB[5] = {F_, 2, 4, 4, F_ / 32}, stB[4] = {r, 8 * r, 2 * r, 32 * r};
            ok = ok && encode(fn, &p.vB, BF, 5, V, dimsB, stB, boxB);
        }
        {
            const cuuint64_t r = D_ * 2;
            const cuuint64_t dimE[5] = {D_, 8, D_ / 8, 1, 2}, stE[4] = {r, 8 * r, 8 * r, 128};
            const cuuint32_t boxE[5] = {64, 8, 8, 1, 2};
            ok = ok && encode(fn, &p.mapB[JOB_X], BF, 5, U, dimE, stE, boxE);
            const cuuint64_t dimsB[5] = {D_, 2, 4, 4, D_ / 32}, stB[4] = {r, 2 * r, 8 * r, 32 * r};
            ok = ok && encode(fn, &p.uB, BF, 5, U, dimsB, stB, boxB);
        }
        p.mapA[JOB_D] = p.mapA[JOB_C];
        p.mapB[JOB_D] = p.mapB[JOB_A];
        for (int i = 0; i < NCTA; i++) p.role[i] = make_role(i);
        for (int i = 0; i < 8; i++) { p.sched[i >> 1][i & 1] = make_sched(i >> 1, i & 1); p.blks[i] = make_blks(i); p.fills[i >> 1] = make_fills(i >> 1); }
        ok = ok && cudaGetSymbolAddress((void**)&p.scr, g_scratch) == cudaSuccess;
        p.scales = scales;
        p.zeros = zeros;
        p.y = y;
    }
    if (ok) {
        kern<<<NCTA, NTHREADS, SMEM_BYTES>>>(p);
    } else {
        fb_gemm<0><<<dim3((D_ + 63) / 64, S_), 64>>>(x, nullptr, nullptr, nullptr, U, nullptr, S_, D_, D_);
        fb_gemm<1><<<dim3(F_ / 128, D_), 128>>>(nullptr, qw, scales, zeros, V, nullptr, D_, F_, F_);
        fb_gemm<2><<<dim3(F_ / 128, S_), 128>>>(nullptr, nullptr, nullptr, nullptr, nullptr, y, S_, F_, D_);
    }
}
```

```cpp
#include <cuda_runtime.h>
#include <cuda_bf16.h>
#include <cuda.h>
#include <stdint.h>

namespace {

constexpr int S_ = 2048, D_ = 448, F_ = 1792;
constexpr int NCTA = 132;
constexpr int NTHREADS = 384;
constexpr uint32_t SB = 1024;
constexpr uint32_t BLK = 57344;
constexpr uint32_t STAGE = 20480;
constexpr uint32_t XSTAGE = 32768;
constexpr uint32_t BAR = SB + 4 * BLK;
constexpr uint32_t B_FULL1 = BAR, B_FIRST = BAR + 112, B_FULL = BAR + 120, B_EPOCH = BAR + 184, B_ZOK = BAR + 192, B_EMPTY = BAR + 200, B_REL1 = BAR + 232,
                   B_DONE = BAR + 256, B_SZ = BAR + 296, B_GO = BAR + 304, EPOCH = BAR + 312, SZ = BAR + 320, DBG = SZ + 1792;
constexpr int SMEM_BYTES = DBG + 256 - SB;
__host__ __device__ constexpr uint32_t stage_at(int u) { return (u < 3 ? u + 8 : u - 3) * STAGE; }
#define TGAP 350
#define TGAP2 200
#define TSW 7
#define XGAP 400
#define BGAP 900
#define C0MODE 1
#define C0AT 8
#define C0STEP 6
#define C3LATE 0
#define PKIND 0
#define PSPAN 3
#define PSLEEP 0
#define WSTAG 0
#define XPAR 0
#define B0POS 2
#define COMB 1
#define B0DLY 800
#define DEFER 0
#define QA 0
#define QB 0
#define START 1
#define RGAP 180
#define RGAP0 150
#define RGAP3 0
#define ZMODE 1
#define ZGAP 320
#define ZGAP0 500
__host__ __device__ constexpr int pos2(int s) { return s < 8 ? s : s < 14 ? s + 24 : s < 22 ? s - 6 : s + 16; }
__host__ __device__ constexpr uint32_t tdesc(int i) { return i < 16 ? i * 64 + (1024 << 16) : (i + 16) * 64 + (768 << 16); }

constexpr int C_TICKET = 0, C_T = 1, C_X = 29, C_ZERO = 61, C_COUNT = 93;

struct Scratch {
    __nv_bfloat16 T[56 * 448 * 32];
    uint4 xr[32 * 28 * 128];
    unsigned cnt[C_COUNT * 32];
};
__device__ __align__(1024) Scratch g_scratch;
#define TS(i) do {} while (0)
#define TS2(i) do {} while (0)

enum { JOB_A = 0, JOB_C = 1, JOB_D = 2, JOB_X = 3 };

struct Params {
    Scratch* scr;
    const __nv_bfloat16* scales;
    const __nv_bfloat16* zeros;
    __nv_bfloat16* y;
    uint32_t role[NCTA];
    uint32_t sched[4][2];
    uint32_t fills[4];
    uint32_t blks[8];
    CUtensorMap mapA[4], mapB[4];
    CUtensorMap vB, uB;
};

__device__ __forceinline__ bool elect() {
    uint32_t p;
    asm volatile("{\n.reg .pred p;\nelect.sync _|p, 0xffffffff;\nselp.u32 %0, 1, 0, p;\n}" : "=r"(p));
    return p;
}
__device__ __forceinline__ void mbar_init(uint32_t bar, uint32_t cnt) { asm volatile("mbarrier.init.shared::cta.b64 [%0], %1;" ::"r"(bar), "r"(cnt) : "memory"); }
__device__ __forceinline__ void mbar_init_fence() { asm volatile("fence.mbarrier_init.release.cluster;" ::: "memory"); }
__device__ __forceinline__ void mbar_expect_tx(uint32_t bar, uint32_t bytes) { asm volatile("mbarrier.arrive.expect_tx.shared::cta.b64 _, [%0], %1;" ::"r"(bar), "r"(bytes) : "memory"); }
__device__ __forceinline__ void mbar_arrive(uint32_t bar) { asm volatile("mbarrier.arrive.shared::cta.b64 _, [%0];" ::"r"(bar) : "memory"); }
__device__ __forceinline__ void mbar_arrive_n(uint32_t bar, uint32_t n) { asm volatile("mbarrier.arrive.shared::cta.b64 _, [%0], %1;" ::"r"(bar), "r"(n) : "memory"); }
__device__ __forceinline__ void mbar_wait(uint32_t bar, uint32_t parity) {
    asm volatile("{\n.reg .pred p;\n.reg .u32 c;\nmov.u32 c, 0;\n"
                 "W_%=:\nmbarrier.try_wait.parity.shared::cta.b64 p, [%0], %1;\nadd.u32 c, c, 1;\nsetp.gt.or.u32 p, c, 0x80000, p;\n@!p bra.uni W_%=;\n}"
                 ::"r"(bar), "r"(parity) : "memory");
}
__device__ __forceinline__ void mbar_wait_unless(uint32_t ok, uint32_t bar, uint32_t parity) {
    asm volatile("{\n.reg .pred p;\n.reg .u32 c;\nsetp.ne.u32 p, %2, 0;\n@p bra.uni D_%=;\nmov.u32 c, 0;\n"
                 "W_%=:\nmbarrier.try_wait.parity.shared::cta.b64 p, [%0], %1;\nadd.u32 c, c, 1;\nsetp.gt.or.u32 p, c, 0x80000, p;\n@!p bra.uni W_%=;\nD_%=:\n}"
                 ::"r"(bar), "r"(parity), "r"(ok) : "memory");
}
__device__ __forceinline__ uint32_t mbar_try(uint32_t bar, uint32_t parity) {
    uint32_t ok;
    asm volatile("{\n.reg .pred p;\nmbarrier.test_wait.parity.shared::cta.b64 p, [%1], %2;\nselp.u32 %0, 1, 0, p;\n}" : "=r"(ok) : "r"(bar), "r"(parity) : "memory");
    return ok;
}
__device__ __forceinline__ void tma2(uint32_t dst, const CUtensorMap* m, int c0, int c1, uint32_t bar) {
    asm volatile("cp.async.bulk.tensor.2d.shared::cluster.global.mbarrier::complete_tx::bytes [%0], [%1, {%3, %4}], [%2];" ::"r"(dst), "l"(m), "r"(bar), "r"(c0), "r"(c1) : "memory");
}
__device__ __forceinline__ void tma5(uint32_t dst, const CUtensorMap* m, int c0, int c2, int c4, uint32_t bar) {
    asm volatile("cp.async.bulk.tensor.5d.shared::cluster.global.mbarrier::complete_tx::bytes [%0], [%1, {%3, %6, %4, %6, %5}], [%2];" ::"r"(dst), "l"(m), "r"(bar), "r"(c0), "r"(c2), "r"(c4), "r"(0) : "memory");
}
__device__ __forceinline__ void bulk_load(uint32_t dst, const void* src, uint32_t bytes, uint32_t bar) {
    asm volatile("cp.async.bulk.shared::cluster.global.mbarrier::complete_tx::bytes [%0], [%1], %2, [%3];" ::"r"(dst), "l"(src), "r"(bytes), "r"(bar) : "memory");
}
__device__ __forceinline__ void fence_gpu() { asm volatile("fence.proxy.async;" ::: "memory"); }
__device__ __forceinline__ void signal(unsigned* p, unsigned n) { asm volatile("red.relaxed.gpu.global.add.u32 [%0], %1;" ::"l"(p), "r"(n) : "memory"); }
__device__ __forceinline__ void poll_ge(const unsigned* p, unsigned target) {
#pragma unroll 1
    for (int it = 0;; it++) {
        unsigned v;
        asm volatile("ld.relaxed.gpu.global.u32 %0, [%1];" : "=r"(v) : "l"(p) : "memory");
        if ((int)(v - target) >= 0) break;
        if (it > (1 << 20)) __trap();
    }
}
__device__ __forceinline__ void poll_lanes(const unsigned* p, unsigned target, uint32_t& seen, int need) {
#pragma unroll 1
    for (int it = 0; !((seen >> need) & 1); it++) {
        unsigned v = target - 1;
        const int l = threadIdx.x & 31;
        if (l >= need && l <= need + PSPAN && l < 4) {
            if (PKIND == 0) asm volatile("ld.relaxed.gpu.global.u32 %0, [%1];" : "=r"(v) : "l"(p) : "memory");
            if (PKIND == 1) asm volatile("ld.relaxed.sys.global.u32 %0, [%1];" : "=r"(v) : "l"(p) : "memory");
            if (PKIND == 2) asm volatile("atom.relaxed.gpu.global.or.b32 %0, [%1], 0;" : "=r"(v) : "l"(p) : "memory");
            if (PKIND == 3) asm volatile("ld.relaxed.gpu.global.L1::no_allocate.L2::evict_first.u32 %0, [%1];" : "=r"(v) : "l"(p) : "memory");
        }
        if (PSLEEP) __nanosleep(PSLEEP);
        seen = __ballot_sync(0xffffffffu, (int)(v - target) >= 0);
        if (it > (1 << 20)) __trap();
    }
}
__device__ __forceinline__ uint32_t clock32() {
    uint32_t c;
    asm volatile("mov.u32 %0, %%clock;" : "=r"(c));
    return c;
}
__device__ __forceinline__ void align_clock(uint32_t q) {
    if (q) {
        const uint32_t t = (clock32() | (q - 1)) + 1;
        while ((int)(clock32() - t) < 0) {}
    }
}
__device__ __forceinline__ void bar_sync(int id) { asm volatile("bar.sync %0, 256;" ::"r"(id) : "memory"); }
__device__ __forceinline__ void bar_arrive(int id) { asm volatile("bar.arrive %0, 256;" ::"r"(id) : "memory"); }
__device__ __forceinline__ void wg_fence() { asm volatile("wgmma.fence.sync.aligned;" ::: "memory"); }
__device__ __forceinline__ void wg_commit() { asm volatile("wgmma.commit_group.sync.aligned;" ::: "memory"); }
template <int N> __device__ __forceinline__ void wg_wait() { asm volatile("wgmma.wait_group.sync.aligned %0;" ::"n"(N) : "memory"); }
__device__ __forceinline__ uint4 lds128(uint32_t a) {
    uint4 v;
    asm volatile("ld.shared.v4.u32 {%0,%1,%2,%3}, [%4];" : "=r"(v.x), "=r"(v.y), "=r"(v.z), "=r"(v.w) : "r"(a) : "memory");
    return v;
}
#define U4O(v) "=r"(v.x), "=r"(v.y), "=r"(v.z), "=r"(v.w)
#define U4IO(v) "+r"(v.x), "+r"(v.y), "+r"(v.z), "+r"(v.w)
__device__ __forceinline__ void lds4_if(uint32_t ok, uint4& a, uint4& b, uint4& c, uint4& d, uint32_t q0, uint32_t q1) {
    asm volatile("{\n.reg .pred p;\nsetp.ne.u32 p, %16, 0;\n"
                 "@p ld.shared.v4.u32 {%0,%1,%2,%3}, [%17];\n@p ld.shared.v4.u32 {%4,%5,%6,%7}, [%17+1024];\n"
                 "@p ld.shared.v4.u32 {%8,%9,%10,%11}, [%18];\n@p ld.shared.v4.u32 {%12,%13,%14,%15}, [%18+1024];\n}"
                 : U4O(a), U4O(b), U4O(c), U4O(d) : "r"(ok), "r"(q0), "r"(q1) : "memory");
}
__device__ __forceinline__ void wait_lds4_unless(uint32_t ok, uint32_t bar, uint4& a, uint4& b, uint4& c, uint4& d, uint32_t q0, uint32_t q1) {
    asm volatile("{\n.reg .pred p;\n.reg .u32 c;\nsetp.ne.u32 p, %16, 0;\n@p bra.uni D_%=;\nmov.u32 c, 0;\n"
                 "W_%=:\nmbarrier.try_wait.parity.shared::cta.b64 p, [%19], 0;\nadd.u32 c, c, 1;\nsetp.gt.or.u32 p, c, 0x80000, p;\n@!p bra.uni W_%=;\n"
                 "ld.shared.v4.u32 {%0,%1,%2,%3}, [%17];\nld.shared.v4.u32 {%4,%5,%6,%7}, [%17+1024];\n"
                 "ld.shared.v4.u32 {%8,%9,%10,%11}, [%18];\nld.shared.v4.u32 {%12,%13,%14,%15}, [%18+1024];\nD_%=:\n}"
                 : U4IO(a), U4IO(b), U4IO(c), U4IO(d) : "r"(ok), "r"(q0), "r"(q1), "r"(bar) : "memory");
}
__device__ __forceinline__ uint32_t lds32(uint32_t a) {
    uint32_t v;
    asm volatile("ld.shared.u32 %0, [%1];" : "=r"(v) : "r"(a) : "memory");
    return v;
}
__device__ __forceinline__ void stg128(void* p, uint32_t x, uint32_t y, uint32_t z, uint32_t w) {
    asm volatile("st.global.v4.u32 [%0], {%1,%2,%3,%4};" ::"l"(p), "r"(x), "r"(y), "r"(z), "r"(w) : "memory");
}
__device__ __forceinline__ void red128(void* p, uint32_t x, uint32_t y, uint32_t z, uint32_t w) {
    asm volatile("red.relaxed.gpu.global.add.noftz.v4.bf16x2 [%0], {%1,%2,%3,%4};" ::"l"(p), "r"(x), "r"(y), "r"(z), "r"(w) : "memory");
}
__device__ __forceinline__ uint32_t pack_bf16(float lo, float hi) {
    uint32_t r;
    asm("cvt.rn.bf16x2.f32 %0, %1, %2;" : "=r"(r) : "f"(hi), "f"(lo));
    return r;
}
__device__ __forceinline__ uint32_t dequant2(uint32_t q0, uint32_t q1, uint32_t z, uint32_t s) {
    uint32_t p = pack_bf16(__int2float_rn((int)q0), __int2float_rn((int)q1)), r;
    asm("sub.rn.bf16x2 %0, %1, %2;" : "=r"(r) : "r"(p), "r"(z));
    asm("mul.rn.bf16x2 %0, %1, %2;" : "=r"(p) : "r"(r), "r"(s));
    return p;
}
__device__ __forceinline__ uint32_t bdesc(uint32_t addr, uint32_t lbo) { return (addr >> 4) | ((lbo >> 4) << 16); }
constexpr uint32_t HI128 = 0x40000040, HI64 = 0x80000020;

#define R8(d, o) "=&r"(d[o]), "=&r"(d[o + 1]), "=&r"(d[o + 2]), "=&r"(d[o + 3]), "=&r"(d[o + 4]), "=&r"(d[o + 5]), "=&r"(d[o + 6]), "=&r"(d[o + 7])
#define F8(d, o) "+f"(d[o]), "+f"(d[o + 1]), "+f"(d[o + 2]), "+f"(d[o + 3]), "+f"(d[o + 4]), "+f"(d[o + 5]), "+f"(d[o + 6]), "+f"(d[o + 7])
template <int N, uint32_t HI> __device__ __forceinline__ void mma(float (&d)[N / 2], const uint32_t* a, uint32_t b, int acc) {
    if constexpr (N == 128)
        asm volatile("{\n.reg .pred p;\n.reg .b64 bd;\nsetp.ne.b32 p, %69, 0;\nmov.b64 bd, {%68, %70};\n"
                     "wgmma.mma_async.sync.aligned.m64n128k16.f32.bf16.bf16 "
                     "{%0,%1,%2,%3,%4,%5,%6,%7,%8,%9,%10,%11,%12,%13,%14,%15,%16,%17,%18,%19,%20,%21,%22,%23,%24,%25,%26,%27,%28,%29,%30,%31,"
                     "%32,%33,%34,%35,%36,%37,%38,%39,%40,%41,%42,%43,%44,%45,%46,%47,%48,%49,%50,%51,%52,%53,%54,%55,%56,%57,%58,%59,%60,%61,%62,%63}, "
                     "{%64,%65,%66,%67}, bd, p, 1, 1, 1;\n}\n"
                     : F8(d, 0), F8(d, 8), F8(d, 16), F8(d, 24), F8(d, 32), F8(d, 40), F8(d, 48), F8(d, 56)
                     : "r"(a[0]), "r"(a[1]), "r"(a[2]), "r"(a[3]), "r"(b), "r"(acc), "n"(HI));
    else if constexpr (N == 64)
        asm volatile("{\n.reg .pred p;\n.reg .b64 bd;\nsetp.ne.b32 p, %37, 0;\nmov.b64 bd, {%36, %38};\n"
                     "wgmma.mma_async.sync.aligned.m64n64k16.f32.bf16.bf16 "
                     "{%0,%1,%2,%3,%4,%5,%6,%7,%8,%9,%10,%11,%12,%13,%14,%15,%16,%17,%18,%19,%20,%21,%22,%23,%24,%25,%26,%27,%28,%29,%30,%31}, "
                     "{%32,%33,%34,%35}, bd, p, 1, 1, 1;\n}\n"
                     : F8(d, 0), F8(d, 8), F8(d, 16), F8(d, 24)
                     : "r"(a[0]), "r"(a[1]), "r"(a[2]), "r"(a[3]), "r"(b), "r"(acc), "n"(HI));
    else
        asm volatile("{\n.reg .pred p;\n.reg .b64 bd;\nsetp.ne.b32 p, %21, 0;\nmov.b64 bd, {%20, %22};\n"
                     "wgmma.mma_async.sync.aligned.m64n32k16.f32.bf16.bf16 "
                     "{%0,%1,%2,%3,%4,%5,%6,%7,%8,%9,%10,%11,%12,%13,%14,%15}, "
                     "{%16,%17,%18,%19}, bd, p, 1, 1, 1;\n}\n"
                     : F8(d, 0), F8(d, 8)
                     : "r"(a[0]), "r"(a[1]), "r"(a[2]), "r"(a[3]), "r"(b), "r"(acc), "n"(HI));
}

template <int N, bool P2, class F, class G>
__device__ __forceinline__ void run_block(float (&acc)[N / 2], uint32_t (&A)[112], uint32_t buf, int wg, F mid, G tail) {
    const uint32_t d0 = bdesc(buf, 0);
    wg_fence();
#pragma unroll
    for (int i = 0; i < 28; i++) {
        mid(i);
        if (i == 26) bar_arrive(2 - wg);
        mma<N, P2 ? HI64 : HI128>(acc, &A[4 * i], d0 + (P2 ? tdesc(i) : i * 128), i > 0);
    }
    wg_commit();
    tail();
    wg_wait<0>();
}

template <int NH> __device__ __forceinline__ void pack_rows(const float* acc, uint32_t* v) {
#pragma unroll
    for (int i = 0; i < 2 * NH; i++) {
        const float* a = acc + (NH == 2 ? (i & 1) * 16 + (i >> 1) * 2 : i * 2);
#pragma unroll
        for (int j = 0; j < 4; j++) v[4 * i + j] = pack_bf16(a[4 * j], a[4 * j + 1]);
    }
}
template <int NH> __device__ __forceinline__ void store_y(const float* acc, char* p) {
    uint32_t v[8 * NH];
    pack_rows<NH>(acc, v);
#pragma unroll
    for (int i = 0; i < 2 * NH; i++) stg128(p + (NH == 2 ? (i & 1) * 64 + (i >> 1) * 16 * F_ : i * 16 * F_), v[4 * i], v[4 * i + 1], v[4 * i + 2], v[4 * i + 3]);
}
__device__ __forceinline__ void add_tile(const uint32_t* v, char* p, char* q, uint32_t gap) {
    const uint32_t t = clock32(), o = WSTAG ? ((threadIdx.x >> 5) & 3) * (gap / 4) : 0;
#pragma unroll
    for (int i = 0; i < 4; i++) {
        if (i || WSTAG) while (clock32() - t < i * gap + o) {}
        red128((i & 1 ? q : p) + (i >> 1) * 512, v[4 * i], v[4 * i + 1], v[4 * i + 2], v[4 * i + 3]);
    }
}
template <int NSTEP> __device__ __forceinline__ void store_frag(const float* acc, uint4* p) {
#pragma unroll
    for (int s = 0; s < NSTEP; s++)
        stg128(p + s * 128, pack_bf16(acc[8 * s], acc[8 * s + 1]), pack_bf16(acc[8 * s + 2], acc[8 * s + 3]),
               pack_bf16(acc[8 * s + 4], acc[8 * s + 5]), pack_bf16(acc[8 * s + 6], acc[8 * s + 7]));
}
__device__ __forceinline__ void warp_arrive(uint32_t bar, uint32_t n) {
    __syncwarp();
    if (elect()) mbar_arrive_n(bar, n);
}
template <int I0, int I1> __device__ __forceinline__ void lds_frags(uint32_t (&A)[112], uint32_t a) {
#pragma unroll
    for (int i = I0; i < I1; i++)
        asm volatile("ld.shared.v4.u32 {%0,%1,%2,%3}, [%4];" : "=r"(A[4 * i]), "=r"(A[4 * i + 1]), "=r"(A[4 * i + 2]), "=r"(A[4 * i + 3]) : "r"(a + i * 2048) : "memory");
}

template <bool BY_SMID>
__global__ void __launch_bounds__(NTHREADS, 1) quip_kernel(const __grid_constant__ Params p) {
    const int tid = threadIdx.x, lane = tid & 31;
    uint32_t smid;
    if (BY_SMID) asm volatile("mov.u32 %0, %%smid;" : "=r"(smid));
    else asm volatile("mov.u32 %0, %%ctaid.x;" : "=r"(smid));
    const uint32_t role = __shfl_sync(0xffffffffu, p.role[smid + (tid >> 9)], 0);
    const int warp = __shfl_sync(0xffffffffu, tid >> 5, 0);
    const bool loader = warp == 8 || warp == 11;
    const int odd = warp & 1;
    const int job = role & 3, kq = (role >> 2) & 3, G = (role >> 4) & 7, arow = (role >> 7) & 31;
    const int mt = (role >> 12) & 15, jt = (role >> 16) & 7;
    const bool has_p2 = (role >> 19) & 1, isx = job == JOB_X;
    auto load_stage = [&](int u) {
        const uint32_t dst = SB + (isx ? u * XSTAGE : stage_at(u)), fb = B_FULL1 + 8 * u;
        const int k = isx ? u * 64 : kq * 448 + u * 32;
        tma2(dst + (isx ? 16384 : job == JOB_A ? 4096 : 8192), &p.mapA[job], k, arow * 64, fb);
        tma5(dst, &p.mapB[job], isx ? kq * 112 : 0, k >> 3, G, fb);
        TS2(42 + u);
    };
    if (warp == 8) {
        if (elect()) {
            TS(34);
            mbar_init(B_FULL1, 1);
            mbar_init_fence();
            load_stage(0);
            TS(35);
        }
    } else if (warp == 9) {
        if (elect()) {
            mbar_init(B_SZ, 1);
            mbar_init_fence();
            mbar_expect_tx(B_SZ, 1792);
            bulk_load(SZ, p.zeros + kq * 448, 896, B_SZ);
            bulk_load(SZ + 896, p.scales + kq * 448, 896, B_SZ);
            TS(36);
        }
    }
    const uint32_t c0 = clock32() - (warp == 8 ? 150 : 0);

    if (warp < 8) {
        asm volatile("setmaxnreg.inc.sync.aligned.u32 232;");
        const int wg = warp >> 2, wq = warp & 3, wtid = tid & 127, r0 = wq * 16 + (lane >> 2);
        uint32_t sched = p.sched[job][wg];
        const bool idle1 = sched >> 28;
        uint32_t blks = p.blks[jt] | ((p.fills[job] >> (12 + 3 * wg)) << 24);
        asm volatile("" : "+r"(blks));
        uint32_t A[112];
        if (wg == 1) bar_arrive(1);
        asm volatile("bar.sync 4, 384;" ::: "memory");
#define CTS(i) do { if (wq == 0) TS((i) + 17 * wg); } while (0)
        uint32_t ok1 = 0, ok2 = 0;
        auto peek = [&](uint32_t sc) {
            ok1 = mbar_try(B_FULL + 16 * (sc & 3), (sc >> 2) & 1);
            ok2 = mbar_try(B_FULL + 8 + 16 * (sc & 3), (sc >> 2) & 1);
        };
        auto peek_next = [&]() { peek(sched >> 4); };
        auto next_block = [&]() -> uint32_t {
            mbar_wait_unless(ok1, B_FULL + 16 * (sched & 3), (sched >> 2) & 1);
            bar_sync(1 + wg);
            return SB + (sched & 3) * BLK;
        };
        auto half2 = [&](int i) {
            if (i == 14) {
                mbar_wait_unless(ok2, B_FULL + 8 + 16 * (sched & 3), (sched >> 2) & 1);
                wg_fence();
            }
        };
        uint32_t held[16];
        char *tp = nullptr, *tq = nullptr;
        auto release_block = [&]() {
            if (elect()) mbar_arrive_n(B_EMPTY + 8 * (sched & 3), 1 + ((sched >> 3) & 1));
            sched >>= 4;
        };

        auto no_tile = [&]() {
#pragma unroll
            for (int i = 0; i < 16; i++) asm volatile("" : "=r"(held[i]));
        };
        if (idle1) {
            for (int b = 0; b < 3; b++) { bar_sync(2); bar_arrive(1); }
            no_tile();
        } else if (isx) {
            const uint32_t rowa = SB + 16384 + (wg * 64 + wq * 16 + (lane & 15)) * 128 + (((lane >> 4) ^ (lane & 7)) << 4);
            uint4* dst = p.scr->xr + (arow + wg) * 28 * 128 + wtid;
            {
                float acc[64];
#pragma unroll
                for (int st = 0; st < 7; st++) {
                    mbar_wait(B_FULL1 + 8 * st, 0);
                    if (st == 0) CTS(0);
#pragma unroll
                    for (int ks = 4 * st; ks < 4 * st + 4; ks++)
                        asm volatile("ldmatrix.sync.aligned.m8n8.x4.shared.b16 {%0,%1,%2,%3}, [%4];"
                                     : "=r"(A[4 * ks]), "=r"(A[4 * ks + 1]), "=r"(A[4 * ks + 2]), "=r"(A[4 * ks + 3])
                                     : "r"((rowa ^ ((ks & 3) << 5)) + st * XSTAGE) : "memory");
                    wg_fence();
#pragma unroll
                    for (int ks = 0; ks < 4; ks++) mma<128, HI128>(acc, &A[16 * st + 4 * ks], bdesc(SB + st * XSTAGE + ks * 2048, 8192), st + ks > 0);
                    wg_commit();
                    if (st == 2 || st == 4) {
                        wg_wait<1>();
                        if (elect()) mbar_arrive(B_EMPTY + 4 * (st - 2));
                    }
                    if (st == 2) CTS(13);
                    if (st == 4) CTS(14);
                }
                peek(sched);
                wg_wait<0>();
                if (elect()) { mbar_arrive(B_EMPTY + 16); mbar_arrive(B_EMPTY + 24); }
                CTS(1);
                uint32_t v[32];
#pragma unroll
                for (int i = 0; i < 32; i++) {
                    v[i] = pack_bf16(acc[2 * i], acc[2 * i + 1]);
                    asm volatile("" : "+r"(v[i]));
                }
                auto early = [&]() {
#pragma unroll
                    for (int s = 0; s < 8; s++) stg128(dst + (kq * 4 + s) * 128, v[4 * s], v[4 * s + 1], v[4 * s + 2], v[4 * s + 3]);
                    warp_arrive(B_DONE + 8, 1);
                };
                if (wg) early();
                CTS(2);
                float acc2[32];
                run_block<64, false>(acc2, A, next_block(), wg, half2, [&]() {
                    peek_next();
                    if (!wg) early();
                });
                release_block();
                CTS(5);
                store_frag<4>(acc2, dst + (16 + kq * 3) * 128);
            }
            {
                float acc[16];
                run_block<32, false>(acc, A, next_block() + 64, wg, half2, []() {});
                release_block();
                CTS(6);
                store_frag<2>(acc, dst + (20 + kq * 3) * 128);
                warp_arrive(B_DONE + 16, 1);
            }
            ok1 = ok2 = 0;
            no_tile();
        } else {
            tp = reinterpret_cast<char*>(p.scr->T) + (job == JOB_C ? G + wg : G) * BLK + (pos2((job == JOB_A ? arow + wg : arow) * 4 + wq) * 16 + (lane >> 2)) * 64 +
                       (((lane & 3) ^ (lane >> 3)) << 4);
            tq = tp + (pos2((job == JOB_A ? arow + wg : arow) * 4 + wq) < 16 ? 16384 : 12288);
            const uint32_t nrel1 = job == JOB_D ? 2 : 1;
            {
                const uint32_t q0 = SB + (job == JOB_A ? 4096 + wg * 8192 : 8192) + r0 * 128 + (((2 * (lane & 3)) ^ (lane >> 2)) << 4);
                const uint32_t q1 = q0 ^ 16;
                const uint32_t db = bdesc(SB + (job == JOB_C ? wg * 4096 : 0), 0);
                float acc[32];
                mbar_wait(B_SZ, 0);
#pragma unroll
                for (int i = 0; i < 28; i++) {
                    const uint4 v = lds128(SZ + (lane & 3) * 16 + (i & 1) * 896 + (i >> 1) * 64);
                    A[4 * i] = v.x; A[4 * i + 1] = v.y; A[4 * i + 2] = v.z; A[4 * i + 3] = v.w;
                }
                CTS(12);
                mbar_wait(B_FULL1, 0);
                CTS(0);
                if (warp == 0) TS2(32);
                constexpr uint32_t so0 = stage_at(0);
                uint4 l0 = lds128(q0 + so0), h0 = lds128(q0 + so0 + 1024), l1 = lds128(q1 + so0), h1 = lds128(q1 + so0 + 1024);
                uint32_t ok = mbar_try(B_FULL1 + 8, 0);
#pragma unroll
                for (int st = 0; st < 14; st++) {
                    const uint32_t so = stage_at(st + 1);
                    uint4 m0, i0, m1, i1;
                    if (st < 13) lds4_if(ok, m0, i0, m1, i1, q0 + so, q1 + so);
                    uint32_t ok2 = 0;
                    const uint32_t z0 = A[8 * st], z1 = A[8 * st + 1], z2 = A[8 * st + 2], z3 = A[8 * st + 3];
                    const uint32_t s0 = A[8 * st + 4], s1 = A[8 * st + 5], s2 = A[8 * st + 6], s3 = A[8 * st + 7];
                    A[8 * st + 0] = dequant2(l0.x, l0.y, z0, s0);
                    A[8 * st + 1] = dequant2(h0.x, h0.y, z0, s0);
                    A[8 * st + 2] = dequant2(l0.z, l0.w, z1, s1);
                    A[8 * st + 3] = dequant2(h0.z, h0.w, z1, s1);
                    A[8 * st + 4] = dequant2(l1.x, l1.y, z2, s2);
                    A[8 * st + 5] = dequant2(h1.x, h1.y, z2, s2);
                    A[8 * st + 6] = dequant2(l1.z, l1.w, z3, s3);
                    A[8 * st + 7] = dequant2(h1.z, h1.w, z3, s3);
                    if (st < 12) ok2 = mbar_try(B_FULL1 + 8 * (st + 2), 0);
                    wg_fence();
                    mma<64, HI128>(acc, &A[8 * st], db + (stage_at(st) >> 4), st > 0);
                    mma<64, HI128>(acc, &A[8 * st + 4], db + (stage_at(st) >> 4) + 128, 1);
                    wg_commit();
                    const int r = st - 1;
                    if ((r >= 0 && r < 3) || r == 5 || r == 8 || r == 11) {
                        wg_wait<1>();
                        if (elect()) mbar_arrive_n(r < 3 ? B_REL1 + 8 * r : B_EMPTY + 8 * ((r - 5) / 3), nrel1);
                    }
                    if (warp == 0) TS2(st);
                    if (st < 13) {
                        wait_lds4_unless(ok, B_FULL1 + 8 * (st + 1), m0, i0, m1, i1, q0 + so, q1 + so);
                        l0 = m0; h0 = i0; l1 = m1; h1 = i1;
                    }
                    if (warp == 0) TS2(16 + st);
                    ok = ok2;
                    if (st == 2) CTS(13);
                    if (st == 5) CTS(14);
                    if (st == 9) CTS(15);
                }
                mbar_wait(B_ZOK, 0);
                peek(sched);
                wg_wait<0>();
                if (elect()) mbar_arrive_n(B_EMPTY + 24, nrel1);
                CTS(1);
                pack_rows<2>(acc, held);
                if (wg || !C0MODE) {
                    add_tile(held, tp, tq, wg ? RGAP0 : 0);
                    warp_arrive(B_DONE + 8, nrel1);
                }
                CTS(2);
            }
#pragma unroll 1
            for (int b = 1; b < 4; b++) {
                float acc[32];
                const uint32_t send = b == 1 ? C0MODE && !wg : (DEFER >> (2 * (b - 2) + wg)) & 1;
                run_block<64, false>(acc, A, next_block(), wg, [&](int i) {
                    half2(i);
                    if (i >= C0AT && i < C0AT + 4 * C0STEP && (i - C0AT) % C0STEP == 0) {
                        const int g = (i - C0AT) / C0STEP;
                        asm volatile("{\n.reg .pred p;\nsetp.ne.u32 p, %5, 0;\n@p red.relaxed.gpu.global.add.noftz.v4.bf16x2 [%0], {%1,%2,%3,%4};\n}"
                                     ::"l"((g & 1 ? tq : tp) + (g >> 1) * 512), "r"(held[4 * g]), "r"(held[4 * g + 1]), "r"(held[4 * g + 2]),
                                       "r"(held[4 * g + 3]), "r"(send) : "memory");
                        if (g == 3)
                            asm volatile("{\n.reg .pred p, q;\nelect.sync _|q, 0xffffffff;\nsetp.ne.and.u32 p, %2, 0, q;\n"
                                         "@p mbarrier.arrive.shared::cta.b64 _, [%0], %1;\n}" ::"r"(B_DONE + 8 * b), "r"(nrel1), "r"(send) : "memory");
                    }
                }, peek_next);
                release_block();
                CTS(3 + b);
                tp += 7 * BLK;
                tq += 7 * BLK;
                pack_rows<2>(acc, held);
                if (b < 3 && !((DEFER >> (2 * (b - 1) + wg)) & 1)) {
                    add_tile(held, tp, tq, RGAP);
                    warp_arrive(B_DONE + 8 + 8 * b, nrel1);
                }
            }
        }

        if (has_p2) {
            const uint32_t fa = blks >> 24, abar = B_FULL + 16 * (fa & 3), apar = (fa >> 2) & 1, asrc = SB + (fa & 3) * BLK + wtid * 16;
            mbar_wait(abar, apar);
            CTS(16);
            auto late = [&]() {
                mbar_wait(abar + 8, apar);
                lds_frags<16, 28>(A, asrc);
                if (elect()) mbar_arrive_n(B_EMPTY + 8 * (fa & 3), 2);
            };
            char* const yp = reinterpret_cast<char*>(p.y) + (mt * 128 + wg * 64 + r0) * (F_ * 2) + (lane & 3) * 16;
            auto tail = peek_next;
            auto rest = [&](int i) { half2(i - 2); };
            if (jt < 6) {
#pragma unroll
                for (int g = 0; g < 4; g++)
                    asm volatile("red.relaxed.gpu.global.add.noftz.v4.bf16x2 [%16], {%17,%18,%19,%20};\n"
                                 "ld.volatile.shared.v4.u32 {%0,%1,%2,%3}, [%21];\nld.volatile.shared.v4.u32 {%4,%5,%6,%7}, [%21+2048];\n"
                                 "ld.volatile.shared.v4.u32 {%8,%9,%10,%11}, [%21+4096];\nld.volatile.shared.v4.u32 {%12,%13,%14,%15}, [%21+6144];"
                                 : R8(A, 16 * g), R8(A, 16 * g + 8)
                                 : "l"((g & 1 ? tq : tp) + (g >> 1) * 512), "r"(held[4 * g]), "r"(held[4 * g + 1]), "r"(held[4 * g + 2]),
                                   "r"(held[4 * g + 3]), "r"(asrc + g * 8192) : "memory");
                warp_arrive(B_DONE + 32, 1);
                if (!wg) asm volatile("bar.sync 7, 160;" ::: "memory");
                bar_sync(1 + wg);
                const uint32_t d0 = bdesc(SB + (sched & 3) * BLK, 0);
                float acc[32];
#pragma unroll
                for (int i = 0; i < 28; i++) {
                    if (i == 16) {
                        mbar_wait(B_FULL + 8 + 16 * (sched & 3), (sched >> 2) & 1);
                        late();
                        bar_sync(1 + wg);
                    }
                    if (i % 4 == 0) wg_fence();
                    if (i == 14 || i == 26) bar_arrive(2 - wg);
                    mma<64, HI64>(acc, &A[4 * i], d0 + tdesc(i), i > 0);
                }
                wg_commit();
                tail();
                wg_wait<0>();
                CTS(7);
                store_y<2>(acc, yp + (blks & 63) * 64);
                sched >>= 4;
                blks >>= 6;
            } else {
                if (!isx && !idle1) {
                    add_tile(held, tp, tq, 0);
                    warp_arrive(B_DONE + 32, 2);
                }
                lds_frags<0, 16>(A, asrc);
                late();
            }
#pragma unroll 1
            for (int b = jt < 6; b < 4; b++) {
                const uint32_t buf = next_block();
                if (b == (jt < 6)) {
                    float acc[16];
                    run_block<32, true>(acc, A, buf, wg, rest, tail);
                    CTS(7 + b);
                    store_y<1>(acc, yp + (blks & 63) * 64);
                } else {
                    float acc[32];
                    run_block<64, true>(acc, A, buf, wg, rest, tail);
                    CTS(7 + b);
                    store_y<2>(acc, yp + (blks & 63) * 64);
                }
                sched >>= 4;
                blks >>= 6;
            }
        }
        CTS(11);
    } else {
        asm volatile("setmaxnreg.dec.sync.aligned.u32 40;");
        unsigned* const cnt = p.scr->cnt;
        if (!loader) {
            if (!odd) {
                if (elect()) {
                    for (int i = 0; i < 10; i++) mbar_init(B_FULL + 8 * i, 1);
                    for (int i = 0; i < 12; i++) mbar_init(B_EMPTY + 8 * i, 8);
                    mbar_init(B_GO, 1);
                    mbar_init_fence();
                }
                __syncwarp();
                asm volatile("bar.arrive 5, 96;" ::: "memory");
            }
            asm volatile("bar.sync 4, 384;" ::: "memory");
            unsigned* const zc = cnt + (C_ZERO + (role >> 20)) * 32;
            if (odd) {
                if (elect()) {
                    const unsigned epoch = atomicAdd(cnt + C_TICKET * 32, 1u) / NCTA;
                    asm volatile("st.shared.u32 [%0], %1;" ::"r"(EPOCH), "r"(epoch) : "memory");
                    mbar_arrive(B_EPOCH);
                }
                __syncwarp();
                if (!isx) {
                    mbar_wait(B_FULL1 + 8 * 5, 0);
                    poll_ge(zc, (lds32(EPOCH) + 1) * 4);
                    if (elect()) mbar_arrive(B_ZOK);
                    TS(49);
                }
            }
            else if (!isx) {
                char* const z0 = reinterpret_cast<char*>(p.scr->T) + (kq * 7 + G) * BLK + lane * 16;
#pragma unroll 1
                for (int i = 0; i < 8; i++) {
                    const int o = job == JOB_A ? pos2(arow * 4 + i) : 40 + (i & 3);
                    char* z = z0 + o * 1024 + (job == JOB_C ? (i >> 2) * BLK : 0);
                    while (clock32() - c0 < ZGAP0 + i * ZGAP) {}
                    stg128(z, 0, 0, 0, 0);
                    stg128(z + 512, 0, 0, 0, 0);
                    z += o < 16 ? 16384 : 12288;
                    while (clock32() - c0 < ZGAP0 + i * ZGAP + ZGAP / 2) {}
                    stg128(z, 0, 0, 0, 0);
                    stg128(z + 512, 0, 0, 0, 0);
                }
                __syncwarp();
            }
#pragma unroll 1
            for (int f = isx ? 2 - odd : odd; f < (isx ? 3 : 5); f += 2) {
                unsigned* c = f == 0 ? zc : cnt + (isx ? C_X + arow + f - 1 : C_T + (f - 1) * 7 + G) * 32;
                if (f == 4 && jt < 6) {
                    mbar_wait(B_FIRST, 0);
                    asm volatile("bar.arrive 7, 160;" ::: "memory");
                    TS(38);
                }
                if (f) mbar_wait(B_DONE + 8 * f, 0);
                if (elect()) {
                    TS(50 + 2 * f);
                    fence_gpu();
                    signal(c, f && job == JOB_A ? 2 : 1);
                    if (f && job == JOB_C) signal(c + 32, 1);
                    TS(51 + 2 * f);
                }
                __syncwarp();
            }
        } else {
            if (elect()) {
                for (int i = 0; i < 7; i++) mbar_init(B_FULL1 + 16 * i + 16 - 8 * odd, 1);
                mbar_init_fence();
                for (int i = 0; i < 7; i++) mbar_expect_tx(B_FULL1 + 16 * i + 8 * odd, isx ? XSTAGE : STAGE - 4096 * job);
            }
            __syncwarp();
            asm volatile("bar.arrive 4, 384;" ::: "memory");
#pragma unroll 1
            for (int u = 2 - odd; u < (isx ? 7 : 14); u += 2) {
                if (u == 3 || u == 4) asm volatile("bar.sync 5, 96;" ::: "memory");
                if (u >= 11) mbar_wait(B_REL1 + 8 * (u - 11), 0);
                while (clock32() - c0 < (isx ? u * XGAP : min(u * TGAP, TSW * (TGAP - TGAP2) + u * TGAP2))) {}
                if (elect()) load_stage(u);
            }
            if (!odd) {
                const int nb = isx ? 2 : job == JOB_C ? 6 : 3;
                if (elect()) asm volatile("prefetch.tensormap [%0];" ::"l"(&p.vB + isx) : "memory");
                const uint32_t c1 = clock32();
#pragma unroll 1
                for (int b = 0; b < nb; b++) {
                    const uint32_t dst = SB + (b & 3) * BLK, fb = B_FULL + 16 * (b & 3);
                    const int col = isx ? kq * 112 + 128 + b * 32 : (7 + G + (job == JOB_C ? (b >> 1) * 7 + (b & 1) : b * 7)) * 64;
                    mbar_wait(B_EMPTY + 8 * (b & 3), b >> 2);
                    if (!isx) while (clock32() - c1 < (job == JOB_C ? b >> 1 : b) * BGAP) {}
                    if (C3LATE && job != JOB_C && b == 2) mbar_wait(B_DONE + 8, 0), __nanosleep(C3LATE);
                    if (elect()) {
                        mbar_expect_tx(fb, BLK / 2);
                        mbar_expect_tx(fb + 8, BLK / 2);
                        tma5(dst, &p.vB + isx, col, 0, isx ? 0 : kq * 14, fb);
                        tma5(dst + BLK / 2, &p.vB + isx, col, 0, isx ? 7 : kq * 14 + 7, fb + 8);
                    }
                    if (b < 3) TS2(56 + b);
                }
                TS(40);
                if (has_p2) {
                    uint32_t blks = p.blks[jt], fills = p.fills[job];
                    mbar_wait(B_EPOCH, 0);
                    const unsigned target = (lds32(EPOCH) + 1) * 28;
                    const unsigned* fp = cnt + (C_T + ((blks >> (6 * (lane & 3) + 1)) & 31)) * 32;
                    uint32_t seen = 0;
#pragma unroll 1
                    for (int b = 0; b < 4; b++) {
                        const uint32_t fb = B_FULL + 16 * (fills & 3), f0 = b < (jt < 6) ? B_FIRST : fb, dst = SB + (fills & 3) * BLK;
                        const char* src = reinterpret_cast<const char*>(p.scr->T) + ((blks >> 1) & 31) * BLK;
                        const uint32_t n = b == (jt < 6) ? 4096 : 8192, h = (blks & 1) * 4096;
                        const uint32_t ok = COMB ? mbar_try(B_EMPTY + 8 * (fills & 3), (fills >> 2) & 1) : 0;
                        poll_lanes(fp, target, seen, b);
                        TS(41 + 2 * b);
                        mbar_wait_unless(ok, B_EMPTY + 8 * (fills & 3), (fills >> 2) & 1);
                        if (elect()) {
                            mbar_expect_tx(f0, 4 * n);
                            bulk_load(dst, src + 4 * h, 4 * n, f0);
                            mbar_expect_tx(fb + 8, 3 * n);
                            if (B0DLY && b == 0) { const uint32_t t = clock32(); while (clock32() - t < B0DLY) {} }
                            if (!B0DLY && f0 == B_FIRST) mbar_arrive(B_GO);
                            else bulk_load(dst + 32768, src + 32768 + 3 * h, 3 * n, fb + 8);
                        }
                        TS(42 + 2 * b);
                        blks >>= 6;
                        fills >>= 3;
                    }
                }
            } else {
                mbar_wait(B_EPOCH, 0);
                const unsigned epoch = lds32(EPOCH);
                if (has_p2) {
                    const uint32_t fills = p.fills[job] >> 12;
                    uint32_t seen = 0;
                    mbar_wait(B_DONE + 8, 0);
#pragma unroll 1
                    for (int i = 0; i < 4; i++) {
                        const int w = i & 1, late = i >> 1;
                        const uint32_t f = fills >> (3 * w), fb = B_FULL + 16 * (f & 3) + 8 * late, bytes = late ? 24576 : 32768;
                        if (XPAR) {
                            poll_lanes(cnt + (C_X + mt * 2 + (lane & 1)) * 32, (epoch + 1) * 2, seen, late);
                            if (i == 1) {
                                for (int it = 0; !(seen & 2) && it < 64 && !mbar_try(B_EMPTY + 8 * (f & 3), (f >> 2) & 1); it++) {
                                    uint32_t s2 = 0;
                                    poll_lanes(cnt + (C_X + mt * 2 + (lane & 1)) * 32, (epoch + 1) * 2, s2, 0);
                                    seen = s2;
                                }
                            }
                        } else if (!w) poll_ge(cnt + (C_X + mt * 2 + late) * 32, (epoch + 1) * 2);
                        if (!late) mbar_wait(B_EMPTY + 8 * (f & 3), (f >> 2) & 1);
                        if (elect()) {
                            mbar_expect_tx(fb, bytes);
                            bulk_load(SB + (f & 3) * BLK + late * 32768, p.scr->xr + ((mt * 2 + w) * 28 + late * 16) * 128, bytes, fb);
                        }
                        TS(60 + w * 2 + late);
                        if (!B0DLY && i == B0POS && jt < 6) {
                            const uint32_t q = p.fills[job] & 3;
                            mbar_wait(B_GO, 0);
                            if (elect()) bulk_load(SB + q * BLK + 32768, reinterpret_cast<const char*>(p.scr->T) + jt * BLK + 32768, 24576, B_FULL + 16 * q + 8);
                        }
                    }
                } else {
                    poll_ge(cnt + C_TICKET * 32, (epoch + 1) * NCTA);
                }
            }
        }
    }
}

__device__ __nv_bfloat16 g_fb_xr[S_ * D_];
__device__ __nv_bfloat16 g_fb_T[D_ * F_];
template <int MODE>
__global__ void fb_gemm(const __nv_bfloat16* a, const int* q, const __nv_bfloat16* sc, const __nv_bfloat16* ze, const __nv_bfloat16* b,
                        __nv_bfloat16* c, int M, int N, int K) {
    if (MODE == 0) c = g_fb_xr;
    if (MODE == 1) c = g_fb_T;
    if (MODE == 2) { a = g_fb_xr; b = g_fb_T; }
    const int n = blockIdx.x * blockDim.x + threadIdx.x, m = blockIdx.y;
    if (n >= N) return;
    float acc = 0.f;
    for (int k = 0; k < K; k++) {
        const __nv_bfloat16 av = MODE == 1 ? __hmul(__hsub(__float2bfloat16((float)q[m * K + k]), ze[k]), sc[k]) : a[m * K + k];
        acc += __bfloat162float(av) * __bfloat162float(b[k * N + n]);
    }
    c[m * N + n] = __float2bfloat16(acc);
}

typedef CUresult (*EncodeFn)(CUtensorMap*, CUtensorMapDataType, cuuint32_t, void*, const cuuint64_t*, const cuuint64_t*, const cuuint32_t*,
                             const cuuint32_t*, CUtensorMapInterleave, CUtensorMapSwizzle, CUtensorMapL2promotion, CUtensorMapFloatOOBfill);

bool encode(EncodeFn fn, CUtensorMap* m, CUtensorMapDataType dt, int rank, const void* p, const cuuint64_t* dims, const cuuint64_t* strides,
            const cuuint32_t* box) {
    const cuuint32_t es[5] = {1, 1, 1, 1, 1};
    return fn(m, dt, rank, const_cast<void*>(p), dims, strides, box, es, CU_TENSOR_MAP_INTERLEAVE_NONE, CU_TENSOR_MAP_SWIZZLE_128B,
              CU_TENSOR_MAP_L2_PROMOTION_L2_128B, CU_TENSOR_MAP_FLOAT_OOB_FILL_NONE) == CUDA_SUCCESS;
}

uint32_t make_role(int sm) {
    const int t = sm >> 1;
    int gpc, ti;
    if (t < 32) { gpc = t & 7; ti = t >> 3; }
    else if (t < 60) { gpc = 1 + (t - 32) % 7; ti = 4 + (t - 32) / 7; }
    else if (t < 62) { gpc = t - 54; ti = 8; }
    else { gpc = 0; ti = t - 58; }
    const int idx = ti * 2 + (sm & 1), kq = gpc >> 1;
    auto tjob = [&](int job, int G, int dblk) { return (unsigned)(job | kq << 2 | G << 4 | dblk << 7); };
    auto xjob = [&](int xm, int xh) { return (unsigned)(JOB_X | xh << 3 | xm << 8); };
    unsigned r;
    if (gpc & 1) {
        if (idx < 12) r = tjob(JOB_A, idx & 3, (idx >> 2) * 2);
        else if (idx < 14) r = tjob(JOB_C, (idx - 12) * 2, 6);
        else r = xjob(((0xC852 >> (kq * 4)) & 15) + ((idx - 14) >> 1), idx & 1);
    } else {
        if (idx < 9) r = tjob(JOB_A, 4 + idx % 3, (idx / 3) * 2);
        else if (idx == 9) r = tjob(JOB_C, 4, 6);
        else if (idx == 10) r = tjob(JOB_D, 6, 6);
        else if (idx == 11) r = xjob(14 + (kq >> 1), kq & 1);
        else r = xjob(kq * 3 + ((idx - 12) >> 1), idx & 1);
    }
#define P2MAP 3
    const int n = gpc & 1 ? (idx < 14 ? 10 + idx : 16 + idx) : (idx < 10 ? idx : 14 + idx);
    int mt = kq * 4 + (n & 3), jt = (n >> 2) & 7;
    if (P2MAP == 3) {
        mt = kq * 4 + (n < 24 ? n / 6 : ((n - 24) >> 1) & 3); jt = n < 24 ? n % 6 : 6 + (n & 1);
    }
    return r | mt << 12 | jt << 16 | (idx < 16) << 19 | (unsigned)((gpc & 1) * 16 + (idx & 15)) << 20;
}
uint32_t make_blks(int jt) {
    if (jt < 6) return (unsigned)(2 * jt | (14 + jt) << 6 | 2 * (14 + jt) << 12 | 2 * (21 + jt) << 18);
    return (unsigned)((6 + jt) | 2 * (2 * jt - 2) << 6 | 2 * (2 * jt - 1) << 12 | 2 * (jt == 6 ? 20 : 27) << 18);
}
uint32_t make_fills(int job) {
    const int a[6] = {3, 6, 0, 1, 4, 5}, c[6] = {0, 1, 2, 3, 6, 7}, x[6] = {3, 5, 6, 0, 2, 4};
    const int* f = job == JOB_C ? c : job == JOB_X ? x : a;
    unsigned s = 0;
    for (int i = 0; i < 6; i++) s |= (unsigned)f[i] << (3 * i);
    return s;
}
uint32_t make_sched(int job, int w) {
    const int priv = job == JOB_C || job == JOB_D, nb1 = job == JOB_D && w == 1 ? 0 : job == JOB_X ? 2 : 3;
    unsigned s = (unsigned)(nb1 == 0) << 28;
    for (int b = 0; b < nb1 + 4; b++) {
        const unsigned v = b >= nb1 ? (make_fills(job) >> (3 * (b - nb1))) & 7 : job == JOB_C ? 2 * b + w : b;
        s |= (v | (priv && b < nb1) << 3) << (4 * b);
    }
    return s;
}

}

extern "C" void kernel_launch(void* const* d_in, const int* in_sizes, int n_in, void* d_out, int out_size) {
    const __nv_bfloat16* x = (const __nv_bfloat16*)d_in[0];
    const int* qw = (const int*)d_in[1];
    const __nv_bfloat16* scales = (const __nv_bfloat16*)d_in[2];
    const __nv_bfloat16* zeros = (const __nv_bfloat16*)d_in[3];
    const __nv_bfloat16* U = (const __nv_bfloat16*)d_in[4];
    const __nv_bfloat16* V = (const __nv_bfloat16*)d_in[5];
    __nv_bfloat16* y = (__nv_bfloat16*)d_out;

    int dev = 0, sms = 0, reserved = 0;
    cudaGetDevice(&dev);
    cudaDeviceGetAttribute(&sms, cudaDevAttrMultiProcessorCount, dev);
    cudaDeviceGetAttribute(&reserved, cudaDevAttrReservedSharedMemoryPerBlock, dev);
    auto kern = sms == NCTA ? quip_kernel<true> : quip_kernel<false>;
    EncodeFn fn = nullptr;
    cudaDriverEntryPointQueryResult qr;
    bool ok = sms >= NCTA && reserved == (int)SB &&
              cudaGetDriverEntryPoint("cuTensorMapEncodeTiled", (void**)&fn, cudaEnableDefault, &qr) == cudaSuccess && fn != nullptr;
    ok = ok && cudaFuncSetAttribute(kern, cudaFuncAttributeMaxDynamicSharedMemorySize, SMEM_BYTES) == cudaSuccess;
    Params p;
    if (ok) {
        const auto BF = CU_TENSOR_MAP_DATA_TYPE_BFLOAT16;
        {
            const cuuint64_t dims[2] = {F_, D_}, st[1] = {F_ * 4};
            const cuuint32_t b128[2] = {32, 128}, b64[2] = {32, 64};
            ok = ok && encode(fn, &p.mapA[JOB_A], CU_TENSOR_MAP_DATA_TYPE_INT32, 2, qw, dims, st, b128);
            ok = ok && encode(fn, &p.mapA[JOB_C], CU_TENSOR_MAP_DATA_TYPE_INT32, 2, qw, dims, st, b64);
            const cuuint64_t dimx[2] = {D_, S_}, stx[1] = {D_ * 2};
            const cuuint32_t boxx[2] = {64, 128};
            ok = ok && encode(fn, &p.mapA[JOB_X], BF, 2, x, dimx, stx, boxx);
        }
        const cuuint32_t boxB[5] = {64, 2, 4, 4, 7};
        {
            const cuuint64_t r = F_ * 2;
            const cuuint64_t dimsE[5] = {64, 2, F_ / 8, 4, F_ / 64}, stE[4] = {r, 8 * r, 2 * r, 128};
            const cuuint32_t boxE1[5] = {64, 2, 4, 4, 1}, boxE2[5] = {64, 2, 4, 4, 2};
            ok = ok && encode(fn, &p.mapB[JOB_A], BF, 5, V, dimsE, stE, boxE1);
            ok = ok && encode(fn, &p.mapB[JOB_C], BF, 5, V, dimsE, stE, boxE2);
            const cuuint64_t dimsB[5] = {F_, 2, 4, 4, F_ / 32}, stB[4] = {r, 8 * r, 2 * r, 32 * r};
            ok = ok && encode(fn, &p.vB, BF, 5, V, dimsB, stB, boxB);
        }
        {
            const cuuint64_t r = D_ * 2;
            const cuuint64_t dimE[5] = {D_, 8, D_ / 8, 1, 2}, stE[4] = {r, 8 * r, 8 * r, 128};
            const cuuint32_t boxE[5] = {64, 8, 8, 1, 2};
            ok = ok && encode(fn, &p.mapB[JOB_X], BF, 5, U, dimE, stE, boxE);
            const cuuint64_t dimsB[5] = {D_, 2, 4, 4, D_ / 32}, stB[4] = {r, 2 * r, 8 * r, 32 * r};
            ok = ok && encode(fn, &p.uB, BF, 5, U, dimsB, stB, boxB);
        }
        p.mapA[JOB_D] = p.mapA[JOB_C];
        p.mapB[JOB_D] = p.mapB[JOB_A];
        for (int i = 0; i < NCTA; i++) p.role[i] = make_role(i);
        for (int i = 0; i < 8; i++) { p.sched[i >> 1][i & 1] = make_sched(i >> 1, i & 1); p.blks[i] = make_blks(i); p.fills[i >> 1] = make_fills(i >> 1); }
        ok = ok && cudaGetSymbolAddress((void**)&p.scr, g_scratch) == cudaSuccess;
        p.scales = scales;
        p.zeros = zeros;
        p.y = y;
    }
    if (ok) {
        kern<<<NCTA, NTHREADS, SMEM_BYTES>>>(p);
    } else {
        fb_gemm<0><<<dim3((D_ + 63) / 64, S_), 64>>>(x, nullptr, nullptr, nullptr, U, nullptr, S_, D_, D_);
        fb_gemm<1><<<dim3(F_ / 128, D_), 128>>>(nullptr, qw, scales, zeros, V, nullptr, D_, F_, F_);
        fb_gemm<2><<<dim3(F_ / 128, S_), 128>>>(nullptr, nullptr, nullptr, nullptr, nullptr, y, S_, F_, D_);
    }
}
```

```cpp
#include <cuda_runtime.h>
#include <cuda_bf16.h>
#include <cuda.h>
#include <stdint.h>

namespace {

constexpr int S_ = 2048, D_ = 448, F_ = 1792;
constexpr int NCTA = 132;
constexpr int NTHREADS = 384;
constexpr uint32_t SB = 1024;
constexpr uint32_t BLK = 57344;
constexpr uint32_t STAGE = 20480;
constexpr uint32_t XSTAGE = 32768;
constexpr uint32_t BAR = SB + 4 * BLK;
constexpr uint32_t B_FULL1 = BAR, B_FIRST = BAR + 112, B_FULL = BAR + 120, B_EPOCH = BAR + 184, B_ZOK = BAR + 192, B_EMPTY = BAR + 200, B_REL1 = BAR + 232,
                   B_DONE = BAR + 256, B_SZ = BAR + 296, B_GO = BAR + 304, EPOCH = BAR + 312, B_PUBD = BAR + 320, SZ = BAR + 352, DBG = SZ + 1792;
constexpr int SMEM_BYTES = DBG + 256 - SB;
__host__ __device__ constexpr uint32_t stage_at(int u) { return (u < 3 ? u + 8 : u - 3) * STAGE; }
#define TGAP 350
#define TGAP2 200
#define TSW 7
#define XGAP 400
#define BGAP 900
#define C0MODE 1
#define C0AT 8
#define C0STEP 6
#define C3LATE 0
#define PRE0 16
#define PRE1 16
#define SENDAT -1
#define PSPAN 3
#define PGATE 0
#define WSTAG 0
#define XPAR 0
#define XAT 12
#define XSTEP 2
#define TOFF 0
#define XSW 7
#define XGAP2 XGAP
#define BGAP0 0
#define S1GAP 450
#define CEARLY 1
#define B0DLYC 300
#define RGAP2 100
#define B0DLY 800
#define DEFER 0
#define QA 0
#define QB 0
#define START 1
#define RGAP 180
#define RGAP0 150
#define RGAP3 0
#define ZMODE 1
#define ZGAP 320
#define ZGAP0 500
__host__ __device__ constexpr int pos2(int s) { return s < 8 ? s : s < 20 ? s + 24 : s - 12; }
__host__ __device__ constexpr uint32_t tdesc(int i) { return i < 16 ? i * 64 + (1024 << 16) : (i + 16) * 64 + (768 << 16); }

constexpr int C_TICKET = 0, C_T = 1, C_X = 29, C_ZERO = 61, C_COUNT = 93;

struct Scratch {
    __nv_bfloat16 T[56 * 448 * 32];
    uint4 xr[32 * 28 * 128];
    unsigned cnt[C_COUNT * 32];
};
__device__ __align__(1024) Scratch g_scratch;
#define TS(i) do {} while (0)
#define TS2(i) do {} while (0)

enum { JOB_A = 0, JOB_C = 1, JOB_D = 2, JOB_X = 3 };

struct Params {
    Scratch* scr;
    const __nv_bfloat16* scales;
    const __nv_bfloat16* zeros;
    __nv_bfloat16* y;
    uint32_t role[NCTA];
    uint32_t sched[4][2];
    uint32_t fills[4];
    uint32_t blks[8][2];
    CUtensorMap mapA[4], mapB[4];
    CUtensorMap vB, uB;
};

__device__ __forceinline__ bool elect() {
    uint32_t p;
    asm volatile("{\n.reg .pred p;\nelect.sync _|p, 0xffffffff;\nselp.u32 %0, 1, 0, p;\n}" : "=r"(p));
    return p;
}
__device__ __forceinline__ void mbar_init(uint32_t bar, uint32_t cnt) { asm volatile("mbarrier.init.shared::cta.b64 [%0], %1;" ::"r"(bar), "r"(cnt) : "memory"); }
__device__ __forceinline__ void mbar_init_fence() { asm volatile("fence.mbarrier_init.release.cluster;" ::: "memory"); }
__device__ __forceinline__ void mbar_expect_tx(uint32_t bar, uint32_t bytes) { asm volatile("mbarrier.arrive.expect_tx.shared::cta.b64 _, [%0], %1;" ::"r"(bar), "r"(bytes) : "memory"); }
__device__ __forceinline__ void mbar_arrive(uint32_t bar) { asm volatile("mbarrier.arrive.shared::cta.b64 _, [%0];" ::"r"(bar) : "memory"); }
__device__ __forceinline__ void mbar_arrive_n(uint32_t bar, uint32_t n) { asm volatile("mbarrier.arrive.shared::cta.b64 _, [%0], %1;" ::"r"(bar), "r"(n) : "memory"); }
__device__ __forceinline__ void mbar_wait(uint32_t bar, uint32_t parity) {
    asm volatile("{\n.reg .pred p;\n.reg .u32 c;\nmov.u32 c, 0;\n"
                 "W_%=:\nmbarrier.try_wait.parity.shared::cta.b64 p, [%0], %1;\nadd.u32 c, c, 1;\nsetp.gt.or.u32 p, c, 0x80000, p;\n@!p bra.uni W_%=;\n}"
                 ::"r"(bar), "r"(parity) : "memory");
}
__device__ __forceinline__ void mbar_wait_unless(uint32_t ok, uint32_t bar, uint32_t parity) {
    asm volatile("{\n.reg .pred p;\n.reg .u32 c;\nsetp.ne.u32 p, %2, 0;\n@p bra.uni D_%=;\nmov.u32 c, 0;\n"
                 "W_%=:\nmbarrier.try_wait.parity.shared::cta.b64 p, [%0], %1;\nadd.u32 c, c, 1;\nsetp.gt.or.u32 p, c, 0x80000, p;\n@!p bra.uni W_%=;\nD_%=:\n}"
                 ::"r"(bar), "r"(parity), "r"(ok) : "memory");
}
__device__ __forceinline__ uint32_t mbar_try(uint32_t bar, uint32_t parity) {
    uint32_t ok;
    asm volatile("{\n.reg .pred p;\nmbarrier.test_wait.parity.shared::cta.b64 p, [%1], %2;\nselp.u32 %0, 1, 0, p;\n}" : "=r"(ok) : "r"(bar), "r"(parity) : "memory");
    return ok;
}
__device__ __forceinline__ void tma2(uint32_t dst, const CUtensorMap* m, int c0, int c1, uint32_t bar) {
    asm volatile("cp.async.bulk.tensor.2d.shared::cluster.global.mbarrier::complete_tx::bytes [%0], [%1, {%3, %4}], [%2];" ::"r"(dst), "l"(m), "r"(bar), "r"(c0), "r"(c1) : "memory");
}
__device__ __forceinline__ void tma5(uint32_t dst, const CUtensorMap* m, int c0, int c2, int c4, uint32_t bar) {
    asm volatile("cp.async.bulk.tensor.5d.shared::cluster.global.mbarrier::complete_tx::bytes [%0], [%1, {%3, %6, %4, %6, %5}], [%2];" ::"r"(dst), "l"(m), "r"(bar), "r"(c0), "r"(c2), "r"(c4), "r"(0) : "memory");
}
__device__ __forceinline__ void bulk_load(uint32_t dst, const void* src, uint32_t bytes, uint32_t bar) {
    asm volatile("cp.async.bulk.shared::cluster.global.mbarrier::complete_tx::bytes [%0], [%1], %2, [%3];" ::"r"(dst), "l"(src), "r"(bytes), "r"(bar) : "memory");
}
__device__ __forceinline__ void fence_gpu() { asm volatile("fence.proxy.async;" ::: "memory"); }
__device__ __forceinline__ void signal(unsigned* p, unsigned n) { asm volatile("red.relaxed.gpu.global.add.u32 [%0], %1;" ::"l"(p), "r"(n) : "memory"); }
__device__ __forceinline__ void poll_ge(const unsigned* p, unsigned target) {
#pragma unroll 1
    for (int it = 0;; it++) {
        unsigned v;
        asm volatile("ld.relaxed.gpu.global.u32 %0, [%1];" : "=r"(v) : "l"(p) : "memory");
        if ((int)(v - target) >= 0) break;
        if (it > (1 << 20)) __trap();
    }
}
__device__ __forceinline__ void poll_lanes(const unsigned* p, unsigned target, uint32_t& seen, int need) {
#pragma unroll 1
    for (int it = 0; !((seen >> need) & 1); it++) {
        unsigned v = target - 1;
        const int l = threadIdx.x & 31;
        if (l >= need && l <= need + PSPAN && l < 4) asm volatile("ld.relaxed.gpu.global.u32 %0, [%1];" : "=r"(v) : "l"(p) : "memory");
        seen = __ballot_sync(0xffffffffu, (int)(v - target) >= 0);
        if (it > (1 << 20)) __trap();
    }
}
__device__ __forceinline__ uint32_t clock32() {
    uint32_t c;
    asm volatile("mov.u32 %0, %%clock;" : "=r"(c));
    return c;
}
__device__ __forceinline__ void align_clock(uint32_t q) {
    if (q) {
        const uint32_t t = (clock32() | (q - 1)) + 1;
        while ((int)(clock32() - t) < 0) {}
    }
}
__device__ __forceinline__ void bar_sync(int id) { asm volatile("bar.sync %0, 256;" ::"r"(id) : "memory"); }
__device__ __forceinline__ void bar_arrive(int id) { asm volatile("bar.arrive %0, 256;" ::"r"(id) : "memory"); }
__device__ __forceinline__ void wg_fence() { asm volatile("wgmma.fence.sync.aligned;" ::: "memory"); }
__device__ __forceinline__ void wg_commit() { asm volatile("wgmma.commit_group.sync.aligned;" ::: "memory"); }
template <int N> __device__ __forceinline__ void wg_wait() { asm volatile("wgmma.wait_group.sync.aligned %0;" ::"n"(N) : "memory"); }
__device__ __forceinline__ uint4 lds128(uint32_t a) {
    uint4 v;
    asm volatile("ld.shared.v4.u32 {%0,%1,%2,%3}, [%4];" : "=r"(v.x), "=r"(v.y), "=r"(v.z), "=r"(v.w) : "r"(a) : "memory");
    return v;
}
#define U4O(v) "=r"(v.x), "=r"(v.y), "=r"(v.z), "=r"(v.w)
#define U4IO(v) "+r"(v.x), "+r"(v.y), "+r"(v.z), "+r"(v.w)
__device__ __forceinline__ void lds4_if(uint32_t ok, uint4& a, uint4& b, uint4& c, uint4& d, uint32_t q0, uint32_t q1) {
    asm volatile("{\n.reg .pred p;\nsetp.ne.u32 p, %16, 0;\n"
                 "@p ld.shared.v4.u32 {%0,%1,%2,%3}, [%17];\n@p ld.shared.v4.u32 {%4,%5,%6,%7}, [%17+1024];\n"
                 "@p ld.shared.v4.u32 {%8,%9,%10,%11}, [%18];\n@p ld.shared.v4.u32 {%12,%13,%14,%15}, [%18+1024];\n}"
                 : U4O(a), U4O(b), U4O(c), U4O(d) : "r"(ok), "r"(q0), "r"(q1) : "memory");
}
__device__ __forceinline__ void wait_lds4_unless(uint32_t ok, uint32_t bar, uint4& a, uint4& b, uint4& c, uint4& d, uint32_t q0, uint32_t q1) {
    asm volatile("{\n.reg .pred p;\n.reg .u32 c;\nsetp.ne.u32 p, %16, 0;\n@p bra.uni D_%=;\nmov.u32 c, 0;\n"
                 "W_%=:\nmbarrier.try_wait.parity.shared::cta.b64 p, [%19], 0;\nadd.u32 c, c, 1;\nsetp.gt.or.u32 p, c, 0x80000, p;\n@!p bra.uni W_%=;\n"
                 "ld.shared.v4.u32 {%0,%1,%2,%3}, [%17];\nld.shared.v4.u32 {%4,%5,%6,%7}, [%17+1024];\n"
                 "ld.shared.v4.u32 {%8,%9,%10,%11}, [%18];\nld.shared.v4.u32 {%12,%13,%14,%15}, [%18+1024];\nD_%=:\n}"
                 : U4IO(a), U4IO(b), U4IO(c), U4IO(d) : "r"(ok), "r"(q0), "r"(q1), "r"(bar) : "memory");
}
__device__ __forceinline__ uint32_t lds32(uint32_t a) {
    uint32_t v;
    asm volatile("ld.shared.u32 %0, [%1];" : "=r"(v) : "r"(a) : "memory");
    return v;
}
__device__ __forceinline__ void stg128(void* p, uint32_t x, uint32_t y, uint32_t z, uint32_t w) {
    asm volatile("st.global.v4.u32 [%0], {%1,%2,%3,%4};" ::"l"(p), "r"(x), "r"(y), "r"(z), "r"(w) : "memory");
}
__device__ __forceinline__ void red128(void* p, uint32_t x, uint32_t y, uint32_t z, uint32_t w) {
    asm volatile("red.relaxed.gpu.global.add.noftz.v4.bf16x2 [%0], {%1,%2,%3,%4};" ::"l"(p), "r"(x), "r"(y), "r"(z), "r"(w) : "memory");
}
__device__ __forceinline__ uint32_t pack_bf16(float lo, float hi) {
    uint32_t r;
    asm("cvt.rn.bf16x2.f32 %0, %1, %2;" : "=r"(r) : "f"(hi), "f"(lo));
    return r;
}
__device__ __forceinline__ uint32_t dequant2(uint32_t q0, uint32_t q1, uint32_t z, uint32_t s) {
    uint32_t p = pack_bf16(__int2float_rn((int)q0), __int2float_rn((int)q1)), r;
    asm("sub.rn.bf16x2 %0, %1, %2;" : "=r"(r) : "r"(p), "r"(z));
    asm("mul.rn.bf16x2 %0, %1, %2;" : "=r"(p) : "r"(r), "r"(s));
    return p;
}
__device__ __forceinline__ uint32_t bdesc(uint32_t addr, uint32_t lbo) { return (addr >> 4) | ((lbo >> 4) << 16); }
constexpr uint32_t HI128 = 0x40000040, HI64 = 0x80000020;

#define R8(d, o) "=&r"(d[o]), "=&r"(d[o + 1]), "=&r"(d[o + 2]), "=&r"(d[o + 3]), "=&r"(d[o + 4]), "=&r"(d[o + 5]), "=&r"(d[o + 6]), "=&r"(d[o + 7])
#define F8(d, o) "+f"(d[o]), "+f"(d[o + 1]), "+f"(d[o + 2]), "+f"(d[o + 3]), "+f"(d[o + 4]), "+f"(d[o + 5]), "+f"(d[o + 6]), "+f"(d[o + 7])
template <int N, uint32_t HI> __device__ __forceinline__ void mma(float (&d)[N / 2], const uint32_t* a, uint32_t b, int acc) {
    if constexpr (N == 128)
        asm volatile("{\n.reg .pred p;\n.reg .b64 bd;\nsetp.ne.b32 p, %69, 0;\nmov.b64 bd, {%68, %70};\n"
                     "wgmma.mma_async.sync.aligned.m64n128k16.f32.bf16.bf16 "
                     "{%0,%1,%2,%3,%4,%5,%6,%7,%8,%9,%10,%11,%12,%13,%14,%15,%16,%17,%18,%19,%20,%21,%22,%23,%24,%25,%26,%27,%28,%29,%30,%31,"
                     "%32,%33,%34,%35,%36,%37,%38,%39,%40,%41,%42,%43,%44,%45,%46,%47,%48,%49,%50,%51,%52,%53,%54,%55,%56,%57,%58,%59,%60,%61,%62,%63}, "
                     "{%64,%65,%66,%67}, bd, p, 1, 1, 1;\n}\n"
                     : F8(d, 0), F8(d, 8), F8(d, 16), F8(d, 24), F8(d, 32), F8(d, 40), F8(d, 48), F8(d, 56)
                     : "r"(a[0]), "r"(a[1]), "r"(a[2]), "r"(a[3]), "r"(b), "r"(acc), "n"(HI));
    else if constexpr (N == 64)
        asm volatile("{\n.reg .pred p;\n.reg .b64 bd;\nsetp.ne.b32 p, %37, 0;\nmov.b64 bd, {%36, %38};\n"
                     "wgmma.mma_async.sync.aligned.m64n64k16.f32.bf16.bf16 "
                     "{%0,%1,%2,%3,%4,%5,%6,%7,%8,%9,%10,%11,%12,%13,%14,%15,%16,%17,%18,%19,%20,%21,%22,%23,%24,%25,%26,%27,%28,%29,%30,%31}, "
                     "{%32,%33,%34,%35}, bd, p, 1, 1, 1;\n}\n"
                     : F8(d, 0), F8(d, 8), F8(d, 16), F8(d, 24)
                     : "r"(a[0]), "r"(a[1]), "r"(a[2]), "r"(a[3]), "r"(b), "r"(acc), "n"(HI));
    else
        asm volatile("{\n.reg .pred p;\n.reg .b64 bd;\nsetp.ne.b32 p, %21, 0;\nmov.b64 bd, {%20, %22};\n"
                     "wgmma.mma_async.sync.aligned.m64n32k16.f32.bf16.bf16 "
                     "{%0,%1,%2,%3,%4,%5,%6,%7,%8,%9,%10,%11,%12,%13,%14,%15}, "
                     "{%16,%17,%18,%19}, bd, p, 1, 1, 1;\n}\n"
                     : F8(d, 0), F8(d, 8)
                     : "r"(a[0]), "r"(a[1]), "r"(a[2]), "r"(a[3]), "r"(b), "r"(acc), "n"(HI));
}

template <int N, bool P2, class F, class G>
__device__ __forceinline__ void run_block(float (&acc)[N / 2], uint32_t (&A)[112], uint32_t buf, int wg, F mid, G tail) {
    const uint32_t d0 = bdesc(buf, 0);
    wg_fence();
#pragma unroll
    for (int i = 0; i < 28; i++) {
        mid(i);
        if (i == 26) bar_arrive(2 - wg);
        mma<N, P2 ? HI64 : HI128>(acc, &A[4 * i], d0 + (P2 ? tdesc(i) : i * 128), i > 0);
    }
    wg_commit();
    tail();
    wg_wait<0>();
}

__device__ __forceinline__ void pack_rows(const float* acc, uint32_t* v) {
#pragma unroll
    for (int i = 0; i < 4; i++) {
        const float* a = acc + (i & 1) * 16 + (i >> 1) * 2;
#pragma unroll
        for (int j = 0; j < 4; j++) v[4 * i + j] = pack_bf16(a[4 * j], a[4 * j + 1]);
    }
}
__device__ __forceinline__ void store_y(const float* acc, char* p) {
    uint32_t v[16];
    pack_rows(acc, v);
#pragma unroll
    for (int i = 0; i < 4; i++) stg128(p + (i & 1) * 64 + (i >> 1) * 16 * F_, v[4 * i], v[4 * i + 1], v[4 * i + 2], v[4 * i + 3]);
}
__device__ __forceinline__ void add_tile(const uint32_t* v, char* p, char* q, uint32_t gap) {
    const uint32_t t = clock32(), o = WSTAG ? ((threadIdx.x >> 5) & 3) * (gap / 4) : 0;
#pragma unroll
    for (int i = 0; i < 4; i++) {
        if (i || WSTAG) while (clock32() - t < i * gap + o) {}
        red128((i & 1 ? q : p) + (i >> 1) * 512, v[4 * i], v[4 * i + 1], v[4 * i + 2], v[4 * i + 3]);
    }
}
template <int NSTEP> __device__ __forceinline__ void store_frag(const float* acc, uint4* p) {
#pragma unroll
    for (int s = 0; s < NSTEP; s++)
        stg128(p + s * 128, pack_bf16(acc[8 * s], acc[8 * s + 1]), pack_bf16(acc[8 * s + 2], acc[8 * s + 3]),
               pack_bf16(acc[8 * s + 4], acc[8 * s + 5]), pack_bf16(acc[8 * s + 6], acc[8 * s + 7]));
}
__device__ __forceinline__ void warp_arrive(uint32_t bar, uint32_t n) {
    __syncwarp();
    if (elect()) mbar_arrive_n(bar, n);
}
template <int I0, int I1> __device__ __forceinline__ void lds_frags(uint32_t (&A)[112], uint32_t a) {
#pragma unroll
    for (int i = I0; i < I1; i++)
        asm volatile("ld.shared.v4.u32 {%0,%1,%2,%3}, [%4];" : "=r"(A[4 * i]), "=r"(A[4 * i + 1]), "=r"(A[4 * i + 2]), "=r"(A[4 * i + 3]) : "r"(a + i * 2048) : "memory");
}

template <bool BY_SMID>
__global__ void __launch_bounds__(NTHREADS, 1) quip_kernel(const __grid_constant__ Params p) {
    const int tid = threadIdx.x, lane = tid & 31;
    uint32_t smid;
    if (BY_SMID) asm volatile("mov.u32 %0, %%smid;" : "=r"(smid));
    else asm volatile("mov.u32 %0, %%ctaid.x;" : "=r"(smid));
    const uint32_t role = __shfl_sync(0xffffffffu, p.role[smid + (tid >> 9)], 0);
    const int warp = __shfl_sync(0xffffffffu, tid >> 5, 0);
    const bool loader = warp == 8 || warp == 11;
    const int odd = warp & 1;
    const int job = role & 3, kq = (role >> 2) & 3, G = (role >> 4) & 7, arow = (role >> 7) & 31;
    const int mt = (role >> 12) & 15, jt = (role >> 16) & 7;
    const bool has_p2 = (role >> 19) & 1, isx = job == JOB_X;
    auto load_stage = [&](int u) {
        const uint32_t dst = SB + (isx ? u * XSTAGE : stage_at(u)), fb = B_FULL1 + 8 * u;
        const int k = isx ? u * 64 : kq * 448 + u * 32;
        tma2(dst + (isx ? 16384 : job == JOB_A ? 4096 : 8192), &p.mapA[job], k, arow * 64, fb);
        tma5(dst, &p.mapB[job], isx ? kq * 160 : 0, k >> 3, G, fb);
        TS2(42 + u);
    };
    const uint32_t cs = clock32();
    if (warp == 8) {
        if (elect()) {
            TS(34);
            mbar_init(B_FULL1, 1);
            mbar_init_fence();
            if (isx || !TOFF) load_stage(0);
            TS(35);
        }
    } else if (warp == 11 && S1GAP) {
        if (elect()) {
            const uint32_t c = clock32();
            mbar_init(B_FULL1 + 8, 1);
            mbar_init_fence();
            if (isx || !TOFF) {
                while (clock32() - c < S1GAP) {}
                load_stage(1);
            }
        }
    } else if (warp == 9) {
        if (elect()) {
            mbar_init(B_SZ, 1);
            mbar_init_fence();
            mbar_expect_tx(B_SZ, 1792);
            bulk_load(SZ, p.zeros + kq * 448, 896, B_SZ);
            bulk_load(SZ + 896, p.scales + kq * 448, 896, B_SZ);
            TS(36);
        }
    }
    const uint32_t c0 = cs + 150;

    if (warp < 8) {
        asm volatile("setmaxnreg.inc.sync.aligned.u32 232;");
        const int wg = warp >> 2, wq = warp & 3, wtid = tid & 127, r0 = wq * 16 + (lane >> 2);
        uint32_t sched = p.sched[job][wg];
        const bool idle1 = sched >> 28;
        uint32_t blks = p.blks[jt][wg] | ((p.fills[job] >> (12 + 3 * wg)) << 24);
        asm volatile("" : "+r"(blks));
        uint32_t A[112];
        if (wg == 1) bar_arrive(1);
        asm volatile("bar.sync 4, 384;" ::: "memory");
#define CTS(i) do { if (wq == 0) TS((i) + 17 * wg); } while (0)
        uint32_t ok1 = 0, ok2 = 0;
        auto peek = [&](uint32_t sc) {
            ok1 = mbar_try(B_FULL + 16 * (sc & 3), (sc >> 2) & 1);
            ok2 = mbar_try(B_FULL + 8 + 16 * (sc & 3), (sc >> 2) & 1);
        };
        auto peek_next = [&]() { peek(sched >> 4); };
        auto next_block = [&]() -> uint32_t {
            mbar_wait_unless(ok1, B_FULL + 16 * (sched & 3), (sched >> 2) & 1);
            bar_sync(1 + wg);
            return SB + (sched & 3) * BLK;
        };
        auto half2 = [&](int i) {
            if (i == 14) {
                mbar_wait_unless(ok2, B_FULL + 8 + 16 * (sched & 3), (sched >> 2) & 1);
                wg_fence();
            }
        };
        const uint32_t fa = blks >> 24, abar = B_FULL + 16 * (fa & 3), apar = (fa >> 2) & 1;
        uint32_t asrc = SB + (fa & 3) * BLK + wtid * 16, oka = 0;
        asm volatile("" : "+r"(asrc));
        float acc3[32];
        uint32_t held[16];
        char *tp = nullptr, *tq = nullptr;
        auto release_block = [&]() {
            if (elect()) mbar_arrive_n(B_EMPTY + 8 * (sched & 3), 1 + ((sched >> 3) & 1));
            sched >>= 4;
        };

        auto no_tile = [&]() {
#pragma unroll
            for (int i = 0; i < 32; i++) asm volatile("" : "=f"(acc3[i]));
        };
        if (idle1) {
            for (int b = 0; b < 3; b++) { bar_sync(2); bar_arrive(1); }
            no_tile();
        } else if (isx) {
            const int mb = wg ^ (kq >> 1);
            const uint32_t rowa = SB + 16384 + (mb * 64 + wq * 16 + (lane & 15)) * 128 + (((lane >> 4) ^ (lane & 7)) << 4);
            uint4* dst = p.scr->xr + (arow + mb) * 28 * 128 + wtid;
            {
                float acc[64];
#pragma unroll
                for (int st = 0; st < 7; st++) {
                    mbar_wait(B_FULL1 + 8 * st, 0);
                    if (st == 0) CTS(0);
#pragma unroll
                    for (int ks = 4 * st; ks < 4 * st + 4; ks++)
                        asm volatile("ldmatrix.sync.aligned.m8n8.x4.shared.b16 {%0,%1,%2,%3}, [%4];"
                                     : "=r"(A[4 * ks]), "=r"(A[4 * ks + 1]), "=r"(A[4 * ks + 2]), "=r"(A[4 * ks + 3])
                                     : "r"((rowa ^ ((ks & 3) << 5)) + st * XSTAGE) : "memory");
                    wg_fence();
#pragma unroll
                    for (int ks = 0; ks < 4; ks++) mma<128, HI128>(acc, &A[16 * st + 4 * ks], bdesc(SB + st * XSTAGE + ks * 2048, 8192), st + ks > 0);
                    wg_commit();
                    if (st == 2 || st == 4) {
                        wg_wait<1>();
                        if (elect()) mbar_arrive(B_EMPTY + 4 * (st - 2));
                    }
                    if (st == 2) CTS(13);
                    if (st == 4) CTS(14);
                }
                peek(sched);
                wg_wait<0>();
                if (elect()) { mbar_arrive(B_EMPTY + 16); mbar_arrive(B_EMPTY + 24); }
                CTS(1);
                uint32_t v[32];
#pragma unroll
                for (int i = 0; i < 32; i++) {
                    v[i] = pack_bf16(acc[2 * i], acc[2 * i + 1]);
                    asm volatile("" : "+r"(v[i]));
                }
                if (wg) {
#pragma unroll
                    for (int s = 0; s < 8; s++) stg128(dst + (kq * 4 + s) * 128, v[4 * s], v[4 * s + 1], v[4 * s + 2], v[4 * s + 3]);
                    warp_arrive(B_DONE + 8, 1);
                }
                CTS(2);
#pragma unroll 1
                for (int b = 0; b < 2 - wg; b++) {
                    float acc2[32];
                    run_block<64, false>(acc2, A, next_block(), wg, [&](int i) {
                        half2(i);
                        if (i >= XAT && i < XAT + 8 * XSTEP && (i - XAT) % XSTEP == 0) {
                            const int s = (i - XAT) / XSTEP;
                            asm volatile("{\n.reg .pred p;\nsetp.eq.u32 p, %5, 0;\n@p st.global.v4.u32 [%0], {%1,%2,%3,%4};\n}"
                                         ::"l"(dst + (kq * 4 + s) * 128), "r"(v[4 * s]), "r"(v[4 * s + 1]), "r"(v[4 * s + 2]), "r"(v[4 * s + 3]), "r"(wg + b) : "memory");
                            if (s == 7)
                                asm volatile("{\n.reg .pred p, q;\nelect.sync _|q, 0xffffffff;\nsetp.eq.and.u32 p, %1, 0, q;\n"
                                             "@p mbarrier.arrive.shared::cta.b64 _, [%0];\n}" ::"r"(B_DONE + 8), "r"(wg + b) : "memory");
                        }
                    }, peek_next);
                    CTS(5 + b);
                    store_frag<4>(acc2, dst + (b ? 20 : 16 + 4 * kq) * 128);
                    release_block();
                }
                warp_arrive(B_DONE + 16, 1);
                if (wg) { bar_sync(2); bar_arrive(1); }
            }
            ok1 = ok2 = 0;
            no_tile();
        } else {
            tp = reinterpret_cast<char*>(p.scr->T) + (job == JOB_C ? G + wg : G) * BLK + (pos2((job == JOB_A ? arow + wg : arow) * 4 + wq) * 16 + (lane >> 2)) * 64 +
                       (((lane & 3) ^ (lane >> 3)) << 4);
            tq = tp + (pos2((job == JOB_A ? arow + wg : arow) * 4 + wq) < 16 ? 16384 : 12288);
            const uint32_t nrel1 = job == JOB_D ? 2 : 1;
            {
                const uint32_t q0 = SB + (job == JOB_A ? 4096 + wg * 8192 : 8192) + r0 * 128 + (((2 * (lane & 3)) ^ (lane >> 2)) << 4);
                const uint32_t q1 = q0 ^ 16;
                const uint32_t db = bdesc(SB + (job == JOB_C ? wg * 4096 : 0), 0);
                float acc[32];
                mbar_wait(B_SZ, 0);
#pragma unroll
                for (int i = 0; i < 28; i++) {
                    const uint4 v = lds128(SZ + (lane & 3) * 16 + (i & 1) * 896 + (i >> 1) * 64);
                    A[4 * i] = v.x; A[4 * i + 1] = v.y; A[4 * i + 2] = v.z; A[4 * i + 3] = v.w;
                }
                CTS(12);
                mbar_wait(B_FULL1, 0);
                CTS(0);
                if (warp == 0) TS2(32);
                constexpr uint32_t so0 = stage_at(0);
                uint4 l0 = lds128(q0 + so0), h0 = lds128(q0 + so0 + 1024), l1 = lds128(q1 + so0), h1 = lds128(q1 + so0 + 1024);
                uint32_t ok = mbar_try(B_FULL1 + 8, 0);
#pragma unroll
                for (int st = 0; st < 14; st++) {
                    const uint32_t so = stage_at(st + 1);
                    uint4 m0, i0, m1, i1;
                    if (st < 13) lds4_if(ok, m0, i0, m1, i1, q0 + so, q1 + so);
                    uint32_t ok2 = 0;
                    const uint32_t z0 = A[8 * st], z1 = A[8 * st + 1], z2 = A[8 * st + 2], z3 = A[8 * st + 3];
                    const uint32_t s0 = A[8 * st + 4], s1 = A[8 * st + 5], s2 = A[8 * st + 6], s3 = A[8 * st + 7];
                    A[8 * st + 0] = dequant2(l0.x, l0.y, z0, s0);
                    A[8 * st + 1] = dequant2(h0.x, h0.y, z0, s0);
                    A[8 * st + 2] = dequant2(l0.z, l0.w, z1, s1);
                    A[8 * st + 3] = dequant2(h0.z, h0.w, z1, s1);
                    A[8 * st + 4] = dequant2(l1.x, l1.y, z2, s2);
                    A[8 * st + 5] = dequant2(h1.x, h1.y, z2, s2);
                    A[8 * st + 6] = dequant2(l1.z, l1.w, z3, s3);
                    A[8 * st + 7] = dequant2(h1.z, h1.w, z3, s3);
                    if (st < 12) ok2 = mbar_try(B_FULL1 + 8 * (st + 2), 0);
                    wg_fence();
                    mma<64, HI128>(acc, &A[8 * st], db + (stage_at(st) >> 4), st > 0);
                    mma<64, HI128>(acc, &A[8 * st + 4], db + (stage_at(st) >> 4) + 128, 1);
                    wg_commit();
                    const int r = st - 1;
                    if ((r >= 0 && r < 3) || r == 5 || r == 8 || r == 11) {
                        wg_wait<1>();
                        if (elect()) mbar_arrive_n(r < 3 ? B_REL1 + 8 * r : B_EMPTY + 8 * ((r - 5) / 3), nrel1);
                    }
                    if (warp == 0) TS2(st);
                    if (st < 13) {
                        wait_lds4_unless(ok, B_FULL1 + 8 * (st + 1), m0, i0, m1, i1, q0 + so, q1 + so);
                        l0 = m0; h0 = i0; l1 = m1; h1 = i1;
                    }
                    if (warp == 0) TS2(16 + st);
                    ok = ok2;
                    if (st == 2) CTS(13);
                    if (st == 5) CTS(14);
                    if (st == 9) CTS(15);
                }
                mbar_wait(B_ZOK, 0);
                peek(sched);
                wg_wait<0>();
                if (elect()) mbar_arrive_n(B_EMPTY + 24, nrel1);
                CTS(1);
                pack_rows(acc, held);
                if (wg || !C0MODE) {
                    add_tile(held, tp, tq, wg ? RGAP0 : 0);
                    warp_arrive(B_DONE + 8, nrel1);
                }
                CTS(2);
            }
#pragma unroll 1
            for (int b = 1;; b++) {
                float (&acc)[32] = acc3;
                const uint32_t send = b == 1 ? C0MODE && !wg : (DEFER >> (2 * (b - 2) + wg)) & 1;
                run_block<64, false>(acc, A, next_block(), wg, [&](int i) {
                    half2(i);
                    if (CEARLY && i == 16) wg_commit();
                    if (i >= C0AT && i < C0AT + 4 * C0STEP && (i - C0AT) % C0STEP == 0) {
                        const int g = (i - C0AT) / C0STEP;
                        asm volatile("{\n.reg .pred p;\nsetp.ne.u32 p, %5, 0;\n@p red.relaxed.gpu.global.add.noftz.v4.bf16x2 [%0], {%1,%2,%3,%4};\n}"
                                     ::"l"((g & 1 ? tq : tp) + (g >> 1) * 512), "r"(held[4 * g]), "r"(held[4 * g + 1]), "r"(held[4 * g + 2]),
                                       "r"(held[4 * g + 3]), "r"(send) : "memory");
                        if (g == 3)
                            asm volatile("{\n.reg .pred p, q;\nelect.sync _|q, 0xffffffff;\nsetp.ne.and.u32 p, %2, 0, q;\n"
                                         "@p mbarrier.arrive.shared::cta.b64 _, [%0], %1;\n}" ::"r"(B_DONE + 8 * b), "r"(nrel1), "r"(send) : "memory");
                    }
                }, [&]() {
                    if (CEARLY) {
                        wg_wait<1>();
                        if (b == 3 && !wg && elect()) mbar_arrive(B_GO);
                    }
                    peek_next();
                    oka = mbar_try(abar, apar);
                    tp += 7 * BLK;
                    tq += 7 * BLK;
                });
                CTS(3 + b);
                if (b == 3) break;
                release_block();
                pack_rows(acc, held);
                if (!((DEFER >> (2 * (b - 1) + wg)) & 1)) {
                    add_tile(held, tp, tq, wg && b == 2 ? RGAP2 : RGAP);
                    warp_arrive(B_DONE + 8 + 8 * b, nrel1);
                }
            }
        }

        if (has_p2) {
            if (jt >= 6 && !isx && !idle1) {
                release_block();
                pack_rows(acc3, held);
                add_tile(held, tp, tq, 0);
                warp_arrive(B_DONE + 32, 2);
            }
            mbar_wait_unless(oka, abar, apar);
            CTS(16);
            auto late = [&]() {
                mbar_wait(abar + 8, apar);
                lds_frags<16, 28>(A, asrc);
                if (elect()) mbar_arrive_n(B_EMPTY + 8 * (fa & 3), 2);
            };
            char* const yp = reinterpret_cast<char*>(p.y) + (mt * 128 + (wg ^ (jt & 1)) * 64 + r0) * (F_ * 2) + (lane & 3) * 16;
            auto tail = peek_next;
            auto rest = [&](int i) { half2(i - 2); };
            if (jt < 6) {
                lds_frags<0, PRE0>(A, asrc);
                release_block();
                pack_rows(acc3, held);
                auto send = [&]() {
#pragma unroll
                    for (int g = 0; g < 4; g++) red128((g & 1 ? tq : tp) + (g >> 1) * 512, held[4 * g], held[4 * g + 1], held[4 * g + 2], held[4 * g + 3]);
                    warp_arrive(B_DONE + 32, 1);
                };
                if (SENDAT < 0) send();
                if (!wg) asm volatile("bar.sync 7, 160;" ::: "memory");
                bar_sync(1 + wg);
                const uint32_t d0 = bdesc(SB + (sched & 3) * BLK, 0);
                float acc[32];
#pragma unroll
                for (int i = 0; i < 28; i++) {
                    if (i == 16) {
                        mbar_wait(B_FULL + 8 + 16 * (sched & 3), (sched >> 2) & 1);
                        late();
                        bar_sync(1 + wg);
                    }
                    if (i == 4) lds_frags<PRE0, PRE1>(A, asrc);
                    if (i == 8) lds_frags<PRE1, 16>(A, asrc);
                    if (i == SENDAT) send();
                    if (i % 4 == 0) wg_fence();
                    if (i == 14 || i == 26) bar_arrive(2 - wg);
                    mma<64, HI64>(acc, &A[4 * i], d0 + tdesc(i), i > 0);
                }
                wg_commit();
                tail();
                wg_wait<0>();
                CTS(7);
                store_y(acc, yp + (blks & 31) * 128);
                sched >>= 4;
                blks >>= 5;
            } else {
                lds_frags<0, 16>(A, asrc);
                late();
            }
#pragma unroll 1
            for (int b = (jt < 6) + wg; b < 4; b++) {
                float acc[32];
                run_block<64, true>(acc, A, next_block(), wg, rest, tail);
                CTS(7 + b);
                store_y(acc, yp + (blks & 31) * 128);
                sched >>= 4;
                blks >>= 5;
            }
        }
        CTS(11);
    } else {
        asm volatile("setmaxnreg.dec.sync.aligned.u32 40;");
        unsigned* const cnt = p.scr->cnt;
        if (!loader) {
            if (!odd) {
                if (elect()) {
                    for (int i = 0; i < 10; i++) mbar_init(B_FULL + 8 * i, 1);
                    for (int i = 0; i < 12; i++) mbar_init(B_EMPTY + 8 * i, 8);
                    mbar_init(B_GO, 4);
                    if (PGATE) for (int i = 0; i < 4; i++) mbar_init(B_PUBD + 8 * i, 1);
                    mbar_init_fence();
                }
                __syncwarp();
                asm volatile("bar.arrive 5, 96;" ::: "memory");
            }
            asm volatile("bar.sync 4, 384;" ::: "memory");
            unsigned* const zc = cnt + (C_ZERO + (role >> 20)) * 32;
            if (odd) {
                if (elect()) {
                    const unsigned epoch = atomicAdd(cnt + C_TICKET * 32, 1u) / NCTA;
                    asm volatile("st.shared.u32 [%0], %1;" ::"r"(EPOCH), "r"(epoch) : "memory");
                    mbar_arrive(B_EPOCH);
                }
                __syncwarp();
                if (!isx) {
                    mbar_wait(B_FULL1 + 8 * 5, 0);
                    poll_ge(zc, (lds32(EPOCH) + 1) * 4);
                    if (elect()) mbar_arrive(B_ZOK);
                    TS(49);
                }
            }
            else if (!isx) {
                char* const z0 = reinterpret_cast<char*>(p.scr->T) + (kq * 7 + G) * BLK + lane * 16;
#pragma unroll 1
                for (int i = 0; i < 8; i++) {
                    const int o = job == JOB_A ? pos2(arow * 4 + i) : 12 + (i & 3);
                    char* z = z0 + o * 1024 + (job == JOB_C ? (i >> 2) * BLK : 0);
                    while ((int)(clock32() - c0) < ZGAP0 + i * ZGAP) {}
                    stg128(z, 0, 0, 0, 0);
                    stg128(z + 512, 0, 0, 0, 0);
                    z += o < 16 ? 16384 : 12288;
                    while ((int)(clock32() - c0) < ZGAP0 + i * ZGAP + ZGAP / 2) {}
                    stg128(z, 0, 0, 0, 0);
                    stg128(z + 512, 0, 0, 0, 0);
                }
                __syncwarp();
            }
#pragma unroll 1
            for (int f = isx ? 2 - odd : odd; f < (isx ? 3 : 5); f += 2) {
                unsigned* c = f == 0 ? zc : cnt + (isx ? C_X + arow + f - 1 : C_T + (f - 1) * 7 + G) * 32;
                if (f == 4 && jt < 6) {
                    mbar_wait(B_FIRST, 0);
                    asm volatile("bar.arrive 7, 160;" ::: "memory");
                    TS(38);
                }
                if (f) mbar_wait(B_DONE + 8 * f, 0);
                if (elect()) {
                    TS(50 + 2 * f);
                    fence_gpu();
                    signal(c, f && job == JOB_A ? 2 : 1);
                    if (f && job == JOB_C) signal(c + 32, 1);
                    if (PGATE && f) mbar_arrive(B_PUBD + 8 * (f - 1));
                    TS(51 + 2 * f);
                }
                __syncwarp();
            }
        } else {
            if (elect()) {
                for (int i = 0; i < 7; i++) if (!(S1GAP && i == 0 && odd)) mbar_init(B_FULL1 + 16 * i + 16 - 8 * odd, 1);
                mbar_init_fence();
                for (int i = 0; i < 7; i++) mbar_expect_tx(B_FULL1 + 16 * i + 8 * odd, isx ? XSTAGE : STAGE - 4096 * job);
            }
            __syncwarp();
            asm volatile("bar.arrive 4, 384;" ::: "memory");
#pragma unroll 1
            for (int u = TOFF && !isx ? odd : 2 + odd; u < (isx ? 7 : 14); u += 2) {
                if (u == 3 || u == 4) asm volatile("bar.sync 5, 96;" ::: "memory");
                if (u >= 11) mbar_wait(B_REL1 + 8 * (u - 11), 0);
                while ((int)(clock32() - c0) < (isx ? max(u * XGAP, XSW * (XGAP - XGAP2) + u * XGAP2) : TOFF + min(u * TGAP, TSW * (TGAP - TGAP2) + u * TGAP2))) {}
                if (elect()) load_stage(u);
            }
            if (!odd) {
                const int nb = isx ? 2 : job == JOB_C ? 6 : 3;
                if (elect()) asm volatile("prefetch.tensormap [%0];" ::"l"(&p.vB + isx) : "memory");
                const uint32_t c1 = clock32();
#pragma unroll 1
                for (int b = 0; b < nb; b++) {
                    const uint32_t dst = SB + (b & 3) * BLK, fb = B_FULL + 16 * (b & 3);
                    const int col = isx ? (b ? 192 : 128 + 64 * kq) : (7 + G + (job == JOB_C ? (b >> 1) * 7 + (b & 1) : b * 7)) * 64;
                    mbar_wait(B_EMPTY + 8 * (b & 3), b >> 2);
                    if (!isx) while (clock32() - c1 < BGAP0 + (job == JOB_C ? b >> 1 : b) * BGAP) {}
                    if (C3LATE && job != JOB_C && b == 2) mbar_wait(B_DONE + 8, 0), __nanosleep(C3LATE);
                    if (elect()) {
                        mbar_expect_tx(fb, BLK / 2);
                        mbar_expect_tx(fb + 8, BLK / 2);
                        tma5(dst, &p.vB + isx, col, 0, isx ? 0 : kq * 14, fb);
                        tma5(dst + BLK / 2, &p.vB + isx, col, 0, isx ? 7 : kq * 14 + 7, fb + 8);
                    }
                    if (b < 3) TS2(56 + b);
                }
                TS(40);
                if (has_p2) {
                    uint32_t blks = p.blks[jt][0], fills = p.fills[job];
                    mbar_wait(B_EPOCH, 0);
                    const unsigned target = (lds32(EPOCH) + 1) * 28;
                    const unsigned* fp = cnt + (C_T + ((blks >> (5 * (lane & 3))) & 31)) * 32;
                    uint32_t seen = 0;
#pragma unroll 1
                    for (int b = 0; b < 4; b++) {
                        const uint32_t fb = B_FULL + 16 * (fills & 3), f0 = b < (jt < 6) ? B_FIRST : fb, dst = SB + (fills & 3) * BLK;
                        const char* src = reinterpret_cast<const char*>(p.scr->T) + (blks & 31) * BLK;
                        const bool go = CEARLY && b == 0 && job == JOB_C;
                        const uint32_t eb = go ? B_GO : B_EMPTY + 8 * (fills & 3), ep = go ? 0 : (fills >> 2) & 1;
                        if (PGATE && jt < 6) mbar_wait(B_PUBD + 8 * b, 0);
                        const uint32_t ok = mbar_try(eb, ep);
                        poll_lanes(fp, target, seen, b);
                        TS(41 + 2 * b);
                        mbar_wait_unless(ok, eb, ep);
                        if (elect()) {
                            mbar_expect_tx(f0, 32768);
                            bulk_load(dst, src, 32768, f0);
                        }
                        if (b == 0) {
                            const uint32_t t = clock32();
                            while (clock32() - t < (job == JOB_C ? B0DLYC : B0DLY)) {}
                            if (CEARLY) mbar_wait(B_EMPTY + 8 * (fills & 3), (fills >> 2) & 1);
                        }
                        if (elect()) {
                            mbar_expect_tx(fb + 8, 24576);
                            bulk_load(dst + 32768, src + 32768, 24576, fb + 8);
                        }
                        TS(42 + 2 * b);
                        blks >>= 5;
                        fills >>= 3;
                    }
                }
            } else {
                mbar_wait(B_EPOCH, 0);
                const unsigned epoch = lds32(EPOCH);
                if (has_p2) {
                    const uint32_t fills = p.fills[job] >> 12;
                    uint32_t seen = 0;
                    mbar_wait(B_DONE + 8, 0);
#pragma unroll 1
                    for (int i = 0; i < 4; i++) {
                        const int w = i & 1, late = i >> 1;
                        const uint32_t f = fills >> (3 * w), fb = B_FULL + 16 * (f & 3) + 8 * late, bytes = late ? 24576 : 32768;
                        if (XPAR) {
                            poll_lanes(cnt + (C_X + mt * 2 + (lane & 1)) * 32, (epoch + 1) * 2, seen, late);
                            if (i == 1) {
                                for (int it = 0; !(seen & 2) && it < 64 && !mbar_try(B_EMPTY + 8 * (f & 3), (f >> 2) & 1); it++) {
                                    uint32_t s2 = 0;
                                    poll_lanes(cnt + (C_X + mt * 2 + (lane & 1)) * 32, (epoch + 1) * 2, s2, 0);
                                    seen = s2;
                                }
                            }
                        } else if (!w) poll_ge(cnt + (C_X + mt * 2 + late) * 32, (epoch + 1) * 2);
                        if (!late) mbar_wait(B_EMPTY + 8 * (f & 3), (f >> 2) & 1);
                        if (elect()) {
                            mbar_expect_tx(fb, bytes);
                            bulk_load(SB + (f & 3) * BLK + late * 32768, p.scr->xr + ((mt * 2 + (w ^ (jt & 1))) * 28 + late * 16) * 128, bytes, fb);
                        }
                        TS(60 + w * 2 + late);
                    }
                } else {
                    poll_ge(cnt + C_TICKET * 32, (epoch + 1) * NCTA);
                }
            }
        }
    }
}

__device__ __nv_bfloat16 g_fb_xr[S_ * D_];
__device__ __nv_bfloat16 g_fb_T[D_ * F_];
template <int MODE>
__global__ void fb_gemm(const __nv_bfloat16* a, const int* q, const __nv_bfloat16* sc, const __nv_bfloat16* ze, const __nv_bfloat16* b,
                        __nv_bfloat16* c, int M, int N, int K) {
    if (MODE == 0) c = g_fb_xr;
    if (MODE == 1) c = g_fb_T;
    if (MODE == 2) { a = g_fb_xr; b = g_fb_T; }
    const int n = blockIdx.x * blockDim.x + threadIdx.x, m = blockIdx.y;
    if (n >= N) return;
    float acc = 0.f;
    for (int k = 0; k < K; k++) {
        const __nv_bfloat16 av = MODE == 1 ? __hmul(__hsub(__float2bfloat16((float)q[m * K + k]), ze[k]), sc[k]) : a[m * K + k];
        acc += __bfloat162float(av) * __bfloat162float(b[k * N + n]);
    }
    c[m * N + n] = __float2bfloat16(acc);
}

typedef CUresult (*EncodeFn)(CUtensorMap*, CUtensorMapDataType, cuuint32_t, void*, const cuuint64_t*, const cuuint64_t*, const cuuint32_t*,
                             const cuuint32_t*, CUtensorMapInterleave, CUtensorMapSwizzle, CUtensorMapL2promotion, CUtensorMapFloatOOBfill);

bool encode(EncodeFn fn, CUtensorMap* m, CUtensorMapDataType dt, int rank, const void* p, const cuuint64_t* dims, const cuuint64_t* strides,
            const cuuint32_t* box) {
    const cuuint32_t es[5] = {1, 1, 1, 1, 1};
    return fn(m, dt, rank, const_cast<void*>(p), dims, strides, box, es, CU_TENSOR_MAP_INTERLEAVE_NONE, CU_TENSOR_MAP_SWIZZLE_128B,
              CU_TENSOR_MAP_L2_PROMOTION_L2_128B, CU_TENSOR_MAP_FLOAT_OOB_FILL_NONE) == CUDA_SUCCESS;
}

uint32_t make_role(int sm) {
    const int t = sm >> 1;
    int gpc, ti;
    if (t < 32) { gpc = t & 7; ti = t >> 3; }
    else if (t < 60) { gpc = 1 + (t - 32) % 7; ti = 4 + (t - 32) / 7; }
    else if (t < 62) { gpc = t - 54; ti = 8; }
    else { gpc = 0; ti = t - 58; }
    const int idx = ti * 2 + (sm & 1), kq = gpc >> 1;
    auto tjob = [&](int job, int G, int dblk) { return (unsigned)(job | kq << 2 | G << 4 | dblk << 7); };
    auto xjob = [&](int xm, int xh) { return (unsigned)(JOB_X | xh << 3 | xm << 8); };
    unsigned r;
    if (gpc & 1) {
        if (idx < 12) r = tjob(JOB_A, idx & 3, (idx >> 2) * 2);
        else if (idx < 14) r = tjob(JOB_C, (idx - 12) * 2, 6);
        else r = xjob(((0xC852 >> (kq * 4)) & 15) + ((idx - 14) >> 1), idx & 1);
    } else {
        if (idx < 9) r = tjob(JOB_A, 4 + idx % 3, (idx / 3) * 2);
        else if (idx == 9) r = tjob(JOB_C, 4, 6);
        else if (idx == 10) r = tjob(JOB_D, 6, 6);
        else if (idx == 11) r = xjob(14 + (kq >> 1), kq & 1);
        else r = xjob(kq * 3 + ((idx - 12) >> 1), idx & 1);
    }
#define P2MAP 3
    const int n = gpc & 1 ? (idx < 14 ? 10 + idx : 16 + idx) : (idx < 10 ? idx : 14 + idx);
    int mt = kq * 4 + (n & 3), jt = (n >> 2) & 7;
    if (P2MAP == 3) {
        mt = kq * 4 + (n < 24 ? n / 6 : ((n - 24) >> 1) & 3); jt = n < 24 ? n % 6 : 6 + (n & 1);
    }
    return r | mt << 12 | jt << 16 | (idx < 16) << 19 | (unsigned)((gpc & 1) * 16 + (idx & 15)) << 20;
}
uint32_t make_blks(int jt, int w) {
    if (jt < 6) return w ? (unsigned)(jt | (14 + jt) << 5 | (21 + jt) << 10) : (unsigned)(jt | (7 + jt / 2) << 5 | (14 + jt) << 10 | (21 + jt) << 15);
    return (unsigned)(6 | (2 * jt - 2) << 5 | (2 * jt - 1) << 10 | (jt == 6 ? 20 : 27) << 15) >> (5 * w);
}
uint32_t make_fills(int job) {
    const int a[6] = {3, 6, 0, 1, 4, 5}, c[6] = {0, 1, 2, 3, 6, 7}, x[6] = {3, 5, 6, 0, 2, 4};
    const int* f = job == JOB_C ? c : job == JOB_X ? x : a;
    unsigned s = 0;
    for (int i = 0; i < 6; i++) s |= (unsigned)f[i] << (3 * i);
    return s;
}
uint32_t make_sched(int job, int w) {
    const int nb1 = job == JOB_D && w == 1 ? 0 : job == JOB_X ? 2 - w : 3;
    unsigned s = (unsigned)(nb1 == 0) << 28;
    int n = 0;
    for (int b = 0; b < nb1; b++) s |= (unsigned)((job == JOB_C ? 2 * b + w : b) | (job == JOB_C || job == JOB_D || (job == JOB_X && b)) << 3) << (4 * n++);
    for (int b = 0; b < 4; b++)
        if (!w || b != (job == JOB_A || job == JOB_C)) s |= ((make_fills(job) >> (3 * b)) & 7) << (4 * n++);
    return s;
}

}

extern "C" void kernel_launch(void* const* d_in, const int* in_sizes, int n_in, void* d_out, int out_size) {
    const __nv_bfloat16* x = (const __nv_bfloat16*)d_in[0];
    const int* qw = (const int*)d_in[1];
    const __nv_bfloat16* scales = (const __nv_bfloat16*)d_in[2];
    const __nv_bfloat16* zeros = (const __nv_bfloat16*)d_in[3];
    const __nv_bfloat16* U = (const __nv_bfloat16*)d_in[4];
    const __nv_bfloat16* V = (const __nv_bfloat16*)d_in[5];
    __nv_bfloat16* y = (__nv_bfloat16*)d_out;

    int dev = 0, sms = 0, reserved = 0;
    cudaGetDevice(&dev);
    cudaDeviceGetAttribute(&sms, cudaDevAttrMultiProcessorCount, dev);
    cudaDeviceGetAttribute(&reserved, cudaDevAttrReservedSharedMemoryPerBlock, dev);
    auto kern = sms == NCTA ? quip_kernel<true> : quip_kernel<false>;
    EncodeFn fn = nullptr;
    cudaDriverEntryPointQueryResult qr;
    bool ok = sms >= NCTA && reserved == (int)SB &&
              cudaGetDriverEntryPoint("cuTensorMapEncodeTiled", (void**)&fn, cudaEnableDefault, &qr) == cudaSuccess && fn != nullptr;
    ok = ok && cudaFuncSetAttribute(kern, cudaFuncAttributeMaxDynamicSharedMemorySize, SMEM_BYTES) == cudaSuccess;
    Params p;
    if (ok) {
        const auto BF = CU_TENSOR_MAP_DATA_TYPE_BFLOAT16;
        {
            const cuuint64_t dims[2] = {F_, D_}, st[1] = {F_ * 4};
            const cuuint32_t b128[2] = {32, 128}, b64[2] = {32, 64};
            ok = ok && encode(fn, &p.mapA[JOB_A], CU_TENSOR_MAP_DATA_TYPE_INT32, 2, qw, dims, st, b128);
            ok = ok && encode(fn, &p.mapA[JOB_C], CU_TENSOR_MAP_DATA_TYPE_INT32, 2, qw, dims, st, b64);
            const cuuint64_t dimx[2] = {D_, S_}, stx[1] = {D_ * 2};
            const cuuint32_t boxx[2] = {64, 128};
            ok = ok && encode(fn, &p.mapA[JOB_X], BF, 2, x, dimx, stx, boxx);
        }
        const cuuint32_t boxB[5] = {64, 2, 4, 4, 7};
        {
            const cuuint64_t r = F_ * 2;
            const cuuint64_t dimsE[5] = {64, 2, F_ / 8, 4, F_ / 64}, stE[4] = {r, 8 * r, 2 * r, 128};
            const cuuint32_t boxE1[5] = {64, 2, 4, 4, 1}, boxE2[5] = {64, 2, 4, 4, 2};
            ok = ok && encode(fn, &p.mapB[JOB_A], BF, 5, V, dimsE, stE, boxE1);
            ok = ok && encode(fn, &p.mapB[JOB_C], BF, 5, V, dimsE, stE, boxE2);
            const cuuint64_t dimsB[5] = {F_, 2, 4, 4, F_ / 32}, stB[4] = {r, 8 * r, 2 * r, 32 * r};
            ok = ok && encode(fn, &p.vB, BF, 5, V, dimsB, stB, boxB);
        }
        {
            const cuuint64_t r = D_ * 2;
            const cuuint64_t dimE[5] = {D_, 8, D_ / 8, 1, 2}, stE[4] = {r, 8 * r, 8 * r, 128};
            const cuuint32_t boxE[5] = {64, 8, 8, 1, 2};
            ok = ok && encode(fn, &p.mapB[JOB_X], BF, 5, U, dimE, stE, boxE);
            const cuuint64_t dimsB[5] = {D_, 2, 4, 4, D_ / 32}, stB[4] = {r, 2 * r, 8 * r, 32 * r};
            ok = ok && encode(fn, &p.uB, BF, 5, U, dimsB, stB, boxB);
        }
        p.mapA[JOB_D] = p.mapA[JOB_C];
        p.mapB[JOB_D] = p.mapB[JOB_A];
        for (int i = 0; i < NCTA; i++) p.role[i] = make_role(i);
        for (int i = 0; i < 8; i++) { p.sched[i >> 1][i & 1] = make_sched(i >> 1, i & 1); p.blks[i][0] = make_blks(i, 0); p.blks[i][1] = make_blks(i, 1); p.fills[i >> 1] = make_fills(i >> 1); }
        ok = ok && cudaGetSymbolAddress((void**)&p.scr, g_scratch) == cudaSuccess;
        p.scales = scales;
        p.zeros = zeros;
        p.y = y;
    }
    if (ok) {
        kern<<<NCTA, NTHREADS, SMEM_BYTES>>>(p);
    } else {
        fb_gemm<0><<<dim3((D_ + 63) / 64, S_), 64>>>(x, nullptr, nullptr, nullptr, U, nullptr, S_, D_, D_);
        fb_gemm<1><<<dim3(F_ / 128, D_), 128>>>(nullptr, qw, scales, zeros, V, nullptr, D_, F_, F_);
        fb_gemm<2><<<dim3(F_ / 128, S_), 128>>>(nullptr, nullptr, nullptr, nullptr, nullptr, y, S_, F_, D_);
    }
}
```
